```python
import torch

def _softmax(x, axis=-1):
    return torch.softmax(x, dim=axis)
def _gelu(x):
    return torch.nn.functional.gelu(x, approximate="tanh")
def _silu(x):
    return torch.nn.functional.silu(x)
def _sigmoid(x):
    return torch.sigmoid(x)
def _layernorm(x, axis=-1, eps=1e-5):
    m = x.mean(dim=axis, keepdim=True)
    v = x.var(dim=axis, keepdim=True, unbiased=False)
    return (x - m) / torch.sqrt(v + eps)
def _scatter_add(tgt, idx, src, axis=0):
    return tgt.clone().index_add_(axis, idx, src)
def _segment_sum(src, seg, n):
    out = torch.zeros((n,) + src.shape[1:], dtype=src.dtype)
    return out.index_add_(0, seg, src)
def _pad(x, pw):
    flat = tuple(v for pair in reversed(pw) for v in pair)
    return torch.nn.functional.pad(x, flat)

kernel_name = 'recurrent_scan__sliding_block_cached__dense_activation_relu__decode'

def setup_inputs():

    _w = (lambda a: (lambda t: t.to(torch.bfloat16) if t.is_floating_point() else t)(torch.as_tensor(a)))
    def _A_setup():
        B, Sq, D = 4, 1, 512
        Hq, Hkv, Sk, Dh = 32, 8, 16384, 128
        assert Hq % Hkv == 0, (Hq, Hkv)
        return {
            "x": _w((lambda *s: torch.randn(*s, dtype=torch.bfloat16) * 0.05)(B, Sq, D)),
            "k_cache": _w((lambda *s: torch.randn(*s, dtype=torch.bfloat16) * 1.6)(B, Hkv, Sk, Dh)),
            "v_cache": _w((lambda *s: torch.randn(*s, dtype=torch.bfloat16) * 0.2)(B, Hkv, Sk, Dh)),
            "wq": _w((lambda *s: torch.randn(*s, dtype=torch.bfloat16) * 1.6)(D, Hq * Dh) * (D ** -0.5)),
            "wo": _w((lambda *s: torch.randn(*s, dtype=torch.bfloat16) * 0.2)(Hq * Dh, D) * ((Hq * Dh) ** -0.5)),
        }
    _A_in = _A_setup()

    def _B_setup():
        B, S, D, Dff = 4, 1, 512, 1792
        return {
            "x": _w((lambda *s: torch.randn(*s, dtype=torch.bfloat16) * 0.05)(B, S, D)),
            "w1": _w((lambda *s: torch.randn(*s, dtype=torch.bfloat16) * 0.1)(D, Dff)),
            "w2": _w((lambda *s: torch.randn(*s, dtype=torch.bfloat16) * 0.1)(Dff, D)),
        }
    _B_in = _B_setup()

    return {
        "A_x": _A_in["x"],
        "A_k_cache": _A_in["k_cache"],
        "A_v_cache": _A_in["v_cache"],
        "A_wq": _A_in["wq"],
        "A_wo": _A_in["wo"],
        "B_x": _B_in["x"],
        "B_w1": _B_in["w1"],
        "B_w2": _B_in["w2"],
    }

def reference(A_x, A_k_cache, A_v_cache, A_wq, A_wo, B_x, B_w1, B_w2):
    def _A_ref(x, k_cache, v_cache, wq, wo):
        B, Sq, D = x.shape
        Hq, Dh = 32, 128
        Hkv, Sk = k_cache.shape[1], k_cache.shape[2]
        W = min(4096, max(256, Sk // 4))
        rep = Hq // Hkv
        q = (lambda x, *d: x.permute(*d))((x @ wq).reshape(B, Sq, Hq, Dh), 0, 2, 1, 3)
        k = (lambda x, n, axis: torch.repeat_interleave(x, n, dim=axis))(k_cache[:, :, Sk - W:, :], rep, axis=1)
        v = (lambda x, n, axis: torch.repeat_interleave(x, n, dim=axis))(v_cache[:, :, Sk - W:, :], rep, axis=1)
        scores = torch.einsum("bhqd,bhkd->bhqk", q, k) * (Dh ** -0.5)
        p = _softmax(scores, axis=-1)
        o = torch.einsum("bhqk,bhkd->bhqd", p, v)
        return (lambda x, *d: x.permute(*d))(o, 0, 2, 1, 3).reshape(B, Sq, Hq * Dh) @ wo

    def _B_ref(x, w1, w2):
        h = torch.einsum("bsd,df->bsf", x, w1)
        zero = torch.zeros_like(h)
        h = torch.maximum(h, zero)
        return torch.einsum("bsf,fd->bsd", h, w2)

    x = A_x
    xn = _layernorm(x, axis=-1)
    s = _A_ref(xn, A_k_cache, A_v_cache, A_wq, A_wo)
    g = _silu(_B_ref(xn, B_w1, B_w2))
    return x + s * g
```

```cpp
#include <cuda_runtime.h>
#include <cuda_bf16.h>
#include <cuda.h>
#include <stdint.h>

#define ILV
#define INFLIGHT 8
#define HINTNS 10000
#define QSLOT 4
#define VGO 99
#define FGO 0
#define SREL 3
#define TAU 652
#define LEADF 10

namespace {

constexpr int NCTA    = 128;
constexpr int NFFN    = 112;
constexpr int NSLOT   = 13;
constexpr int TILE_B  = 16384;
constexpr int NTHREADS = 480;
#define ROT 0
#define KSTEP 256
#define SPSTEP 64
#define TAILJ 100
#define TAILD 2
#define SGO 8
#define SLATE 0
#define SSTAG 300
#define NG 96
#define NPROBE 9
#define PHI (((cta >> 2) * 13) & 31)
constexpr int KT = 16;

constexpr int SEG_XN = 0;
constexpr int SEG_P  = 1024;
constexpr int SEG_H  = 3072;
constexpr int SEG_O  = 3200;
constexpr int SEG_Q  = 3456;
constexpr int ACT_PITCH = 3712 + 16;
constexpr int SM_ACT   = NSLOT * TILE_B;
constexpr int SM_WMAX  = SM_ACT + 4 * ACT_PITCH;
constexpr int SM_LSUM  = SM_WMAX + 128;
constexpr int SM_RED   = SM_LSUM + 32;
constexpr int SM_BAR   = SM_RED + 512;
constexpr int SM_TOTAL = SM_BAR + 2 * NSLOT * 8;
static_assert(SM_TOTAL + 1024 + 256 <= 232448, "smem");

constexpr int BAR_MMA = 1, BAR_XN = 2, BAR_Q = 3, BAR_H = 4, BAR_O = 5, BAR_VGO = 6, BAR_G = 7, BAR_QGO = 8, BAR_SGO = 9, BAR_FGO = 10, BAR_PR = 11, BAR_SREL = 12;

constexpr int MAIL = NCTA * 512;
__device__ __align__(128) float g_mail[2 * MAIL];
__device__ __align__(128) float g_xs[NCTA * 8];
__device__ __align__(4096) float g_arena[1 << 20];
__device__ unsigned g_epoch;
constexpr int AR_O = 0, AR_F = 131072, AR_S = 262144, AR_PROBE = 393216;
constexpr uint32_t HOME_MASK = (1u << 12) | (1u << 13) | (1u << 16) | (1u << 17) | (1u << 19);
__device__ __forceinline__ float* arena_base() {
    return reinterpret_cast<float*>((reinterpret_cast<uintptr_t>(g_arena) + 0x1fffffull) & ~0x1fffffull);
}
__device__ __forceinline__ int slot_off(int producer) { return (producer >> 1) * 2048 + (producer & 1) * 512; }
__device__ __forceinline__ int pick(int off, uint32_t side) { return off + (((__popc(((uint32_t)off << 2) & HOME_MASK) ^ side) & 1) << 10); }

struct Maps { CUtensorMap m[6];
};

#define STAMP(i) do {} while (0)
#define CSTAMP(i) do {} while (0)
#define DSTAMP(i, dep) do {} while (0)
#define VSTAMP(i, val) do {} while (0)
#define PFLUSH(lo, hi) do {} while (0)

constexpr unsigned SPIN_LIMIT = 1u << 22;

__device__ __forceinline__ void mbar_init(uint32_t bar, uint32_t cnt) {
    asm volatile("mbarrier.init.shared::cta.b64 [%0], %1;" :: "r"(bar), "r"(cnt) : "memory");
}
__device__ __forceinline__ void mbar_expect_tx(uint32_t bar, uint32_t bytes) {
    asm volatile("mbarrier.arrive.expect_tx.shared::cta.b64 _, [%0], %1;" :: "r"(bar), "r"(bytes) : "memory");
}
__device__ __forceinline__ void mbar_arrive(uint32_t bar) {
    asm volatile("mbarrier.arrive.shared::cta.b64 _, [%0];" :: "r"(bar) : "memory");
}
__device__ __forceinline__ void mbar_wait(uint32_t bar, uint32_t parity) {
    uint32_t ok, it = 0;
    do {
        asm volatile("{\n .reg .pred p;\n mbarrier.try_wait.parity.shared::cta.b64 p, [%1], %2, %3;\n selp.u32 %0, 1, 0, p;\n}"
                     : "=r"(ok) : "r"(bar), "r"(parity), "r"(HINTNS) : "memory");
        if (++it > SPIN_LIMIT) __trap();
    } while (!ok);
}
__device__ __forceinline__ void tma_tile(uint32_t dst, const CUtensorMap* tm, int row, int half, uint32_t bar, const Maps* mp = nullptr, int fake = -1) {
    asm volatile("cp.async.bulk.tensor.3d.shared::cluster.global.mbarrier::complete_tx::bytes.L2::cache_hint [%0], [%1, {%3, %4, %5}], [%2], %6;"
                 :: "r"(dst), "l"(tm), "r"(bar), "r"(0), "r"(row), "r"(half), "l"(0x12F0000000000000ull) : "memory");
}
__device__ __forceinline__ void ldsm4(uint32_t addr, uint32_t& r0, uint32_t& r1, uint32_t& r2, uint32_t& r3) {
    asm volatile("ldmatrix.sync.aligned.m8n8.x4.shared.b16 {%0,%1,%2,%3}, [%4];"
                 : "=r"(r0), "=r"(r1), "=r"(r2), "=r"(r3) : "r"(addr) : "memory");
}
__device__ __forceinline__ void ldsm4t(uint32_t addr, uint32_t& r0, uint32_t& r1, uint32_t& r2, uint32_t& r3) {
    asm volatile("ldmatrix.sync.aligned.m8n8.x4.trans.shared.b16 {%0,%1,%2,%3}, [%4];"
                 : "=r"(r0), "=r"(r1), "=r"(r2), "=r"(r3) : "r"(addr) : "memory");
}
__device__ __forceinline__ void mma16816(float (&c)[4], uint32_t a0, uint32_t a1, uint32_t a2, uint32_t a3,
                                         uint32_t b0, uint32_t b1) {
    asm volatile("mma.sync.aligned.m16n8k16.row.col.f32.bf16.bf16.f32 {%0,%1,%2,%3}, {%4,%5,%6,%7}, {%8,%9}, {%0,%1,%2,%3};"
                 : "+f"(c[0]), "+f"(c[1]), "+f"(c[2]), "+f"(c[3])
                 : "r"(a0), "r"(a1), "r"(a2), "r"(a3), "r"(b0), "r"(b1));
}
__device__ __forceinline__ void bar_sync(int id, int n) { asm volatile("bar.sync %0, %1;" :: "r"(id), "r"(n) : "memory"); }
__device__ __forceinline__ void bar_arrive(int id, int n) { asm volatile("bar.arrive %0, %1;" :: "r"(id), "r"(n) : "memory"); }
__device__ __forceinline__ unsigned clock32() { unsigned t; asm volatile("mov.u32 %0, %clock;" : "=r"(t)); return t; }
__device__ __forceinline__ unsigned gtime32() { unsigned t; asm volatile("mov.u32 %0, %globaltimer_lo;" : "=r"(t)); return t; }

__device__ __forceinline__ float bf16r(float v) {
    uint32_t d; asm("cvt.rn.bf16x2.f32 %0, %1, %2;" : "=r"(d) : "f"(v), "f"(0.f));
    return __uint_as_float(d);
}
__device__ __forceinline__ uint32_t pack_bf16(float lo, float hi) {
    __nv_bfloat162 t = __floats2bfloat162_rn(lo, hi);
    return *reinterpret_cast<uint32_t*>(&t);
}
__device__ __forceinline__ float bf_lo(uint32_t u) { return __uint_as_float(u << 16); }
__device__ __forceinline__ float bf_hi(uint32_t u) { return __uint_as_float(u & 0xffff0000u); }

__device__ __forceinline__ void put(float* p, float v, uint32_t tag) {
    uint32_t u = (__float_as_uint(v) & ~3u) | tag;
    asm volatile("st.relaxed.gpu.global.u32 [%0], %1;" :: "l"(p), "r"(u) : "memory");
}
__device__ __forceinline__ void put2(float* p, float v0, float v1, uint32_t tag) {
    const uint32_t u0 = (__float_as_uint(v0) & ~3u) | tag, u1 = (__float_as_uint(v1) & ~3u) | tag;
    asm volatile("st.relaxed.gpu.global.v2.u32 [%0], {%1, %2};" :: "l"(p), "r"(u0), "r"(u1) : "memory");
}
__device__ __forceinline__ void clear4(float* p) {
    asm volatile("st.relaxed.gpu.global.v4.u32 [%0], {%1,%1,%1,%1};" :: "l"(p), "r"(0u) : "memory");
}
__device__ __forceinline__ uint4 ld_v4(const float* p) {
    uint4 v;
    asm volatile("ld.relaxed.gpu.global.v4.u32 {%0,%1,%2,%3}, [%4];" : "=r"(v.x), "=r"(v.y), "=r"(v.z), "=r"(v.w) : "l"(p) : "memory");
    return v;
}
__device__ __forceinline__ bool tag_ok(const uint4& v, uint32_t tag) {
    return (((v.x ^ tag) | (v.y ^ tag) | (v.z ^ tag) | (v.w ^ tag)) & 3u) == 0;
}
template <int N>
__device__ __forceinline__ void gather(uint4 (&v)[N], const float* p, int stride, uint32_t tag, int sid = -1) {
    if (sid >= 0) DSTAMP(sid, tag);
#pragma unroll
    for (int i = 0; i < N; i++) v[i] = ld_v4(p + i * stride);
    if (sid >= 0) DSTAMP(sid + 1, v[0].x ^ v[N - 1].x);
    unsigned it = 0;
    while (true) {
        bool all = true;
#pragma unroll
        for (int i = 0; i < N; i++) all = all && tag_ok(v[i], tag);
        if (__all_sync(0xffffffffu, all)) break;
#pragma unroll
        for (int i = 0; i < N; i++) {
            if (!tag_ok(v[i], tag)) v[i] = ld_v4(p + i * stride);
        }
        if (++it > SPIN_LIMIT) __trap();
    }
    if (sid >= 0) { DSTAMP(sid + 2, v[0].x ^ v[N - 1].x); VSTAMP(sid + 3, it + 1); }
}

__device__ __forceinline__ void gather2x2(uint4 (&v)[4], const float* pa, const float* pb, uint32_t tag, int sid) {
    if (sid >= 0) DSTAMP(sid, tag);
    v[0] = ld_v4(pa); v[1] = ld_v4(pa + 512); v[2] = ld_v4(pb); v[3] = ld_v4(pb + 512);
    if (sid >= 0) DSTAMP(sid + 1, v[0].x ^ v[3].x);
    unsigned it = 0;
    while (true) {
        const bool k0 = tag_ok(v[0], tag), k1 = tag_ok(v[1], tag), k2 = tag_ok(v[2], tag), k3 = tag_ok(v[3], tag);
        if (__all_sync(0xffffffffu, k0 && k1 && k2 && k3)) break;
        if (!k0) v[0] = ld_v4(pa);
        if (!k1) v[1] = ld_v4(pa + 512);
        if (!k2) v[2] = ld_v4(pb);
        if (!k3) v[3] = ld_v4(pb + 512);
        if (++it > SPIN_LIMIT) __trap();
    }
    if (sid >= 0) { DSTAMP(sid + 2, v[0].x ^ v[3].x); VSTAMP(sid + 3, it + 1); }
}

struct Ring {
    uint32_t full, empty;
    int slot; uint32_t phase;
    __device__ __forceinline__ void wait() { mbar_wait(full + slot * 8, phase); }
    __device__ __forceinline__ void release(int lane) {
        __syncwarp();
        if (lane == 0) mbar_arrive(empty + slot * 8);
        if (++slot == NSLOT) { slot = 0; phase ^= 1; }
    }
};

__global__ void __launch_bounds__(NTHREADS, 1)
fused_decode_kernel(const __grid_constant__ Maps maps, const __nv_bfloat16* __restrict__ x, __nv_bfloat16* __restrict__ out) {
    extern __shared__ uint8_t smem_raw[];
    const uint32_t sbase = ((uint32_t)__cvta_generic_to_shared(smem_raw) + 1023u) & ~1023u;
    uint8_t* sgen = smem_raw + (sbase - (uint32_t)__cvta_generic_to_shared(smem_raw));
    const int cta = blockIdx.x;
    const int hkv = cta >> 4, rhi = (cta >> 2) & 3, rlo = cta & 3;
    const bool has_ffn = cta < NFFN;
    const uint32_t bar_full = sbase + SM_BAR, bar_empty = bar_full + NSLOT * 8;
    const int kvrow = (rhi * 8 + hkv) * 16384 + 12288 + rlo * SPSTEP;

    if (threadIdx.x - 1u < 31u) return;
    if (threadIdx.x == 0) {
        const unsigned t0 = gtime32();
        STAMP(0);
        mbar_init(bar_full, 1);
        mbar_init(bar_full + 8, 1);
        asm volatile("fence.mbarrier_init.release.cluster;" ::: "memory");
        mbar_expect_tx(bar_full, TILE_B);
        tma_tile(sbase, &maps.m[0], rlo * 128, (cta >> 2) * 2, bar_full, &maps, 0);
#pragma unroll
        for (int i = 2; i < 2 * NSLOT; i++) mbar_init(bar_full + i * 8, i < NSLOT ? 1 : 8);
        asm volatile("fence.mbarrier_init.release.cluster;" ::: "memory");
        asm volatile("barrier.arrive %0, %1;" :: "n"(BAR_XN), "n"(416) : "memory");
        const int n0 = has_ffn ? 3 : 2;
        const int total = 2 * n0 + 2 * KT;
        constexpr int I0 = 1;
        int slot = I0; uint32_t eph = 1;
        int fslot = 0; uint32_t fph = 0;
        int landed = 0;
        const int toff = ((PHI) * TAU) / 32 - (LEADF * TAU) / 16;
#pragma unroll 1
        for (int i = I0; i < total; i++) {
            const int j = (i == 1) ? -2 : i - n0;
            int mi, row, half;
            if (i == 1)             { mi = 0; row = rlo * 128 + 64; half = (cta >> 2) * 2; }
            else if (j < 0)         { mi = 1; row = (cta & 7) * 64; half = (cta >> 3) * 2; }
            else if (j < 2 * KT)    { mi = 2 + (j >> 4); row = kvrow + ((j + ROT) & 15) * KSTEP; half = 0; }
            else if (i < total - 2) { mi = 4; row = (cta >> 2) * 64; half = rlo * 2; }
            else                    { mi = 5; row = (cta >> 2) * 128 + (i - (total - 2)) * 64; half = rlo * 2; }
            {
                const int need = i + 1 - (j >= TAILJ ? TAILD : INFLIGHT);
                while (landed < need) {
                    mbar_wait(bar_full + fslot * 8, fph);
                    if (++fslot == NSLOT) { fslot = 0; fph ^= 1; }
                    landed++;
                }
            }
            if (i >= NSLOT) mbar_wait(bar_empty + slot * 8, eph);
            { const int due = (j + 3) * TAU + toff; while ((int)(gtime32() - t0) < due) {} }
            mbar_expect_tx(bar_full + slot * 8, TILE_B);
            tma_tile(sbase + slot * TILE_B, &maps.m[mi], row, half, bar_full + slot * 8, &maps, mi == 1 ? 2 : mi >= 4 ? 3 + total - i : -1);
            if (++slot == NSLOT) { slot = 0; eph ^= 1; }
            if (i < 6) asm volatile("prefetch.tensormap [%0];" :: "l"(&maps.m[i]) : "memory");
        }
        STAMP(1);
        PFLUSH(0, 2);
    }
    int tix;
    asm volatile("mov.u32 %0, %%tid.x;" : "=r"(tix));
    if (tix == 0) return;
    const int lane = tix & 31;

    const int wix = __shfl_sync(0xffffffffu, tix >> 5, 0);
    if (wix < 5) {
        const int gw = wix - 1;
        {
            const uint4* xr = reinterpret_cast<const uint4*>(x + gw * 512);
            uint4 u0, u1;
            asm volatile("ld.global.nc.v4.u32 {%0,%1,%2,%3}, [%4];" : "=r"(u0.x), "=r"(u0.y), "=r"(u0.z), "=r"(u0.w) : "l"(xr + lane));
            asm volatile("ld.global.nc.v4.u32 {%0,%1,%2,%3}, [%4];" : "=r"(u1.x), "=r"(u1.y), "=r"(u1.z), "=r"(u1.w) : "l"(xr + 32 + lane));
            uint32_t w[8] = {u0.x, u0.y, u0.z, u0.w, u1.x, u1.y, u1.z, u1.w};
            float f[16];
#pragma unroll
            for (int i = 0; i < 8; i++) { f[2 * i] = bf_lo(w[i]); f[2 * i + 1] = bf_hi(w[i]); }
            float s = 0.f;
#pragma unroll
            for (int i = 0; i < 16; i++) s += f[i];
#pragma unroll
            for (int o = 16; o; o >>= 1) s += __shfl_xor_sync(0xffffffffu, s, o);
            const float mean = s * (1.f / 512.f);
            float vs = 0.f;
#pragma unroll
            for (int i = 0; i < 16; i++) { float d = f[i] - mean; vs += d * d; }
#pragma unroll
            for (int o = 16; o; o >>= 1) vs += __shfl_xor_sync(0xffffffffu, vs, o);
            const float mb = bf16r(mean);
            const float den = bf16r(sqrtf(bf16r(bf16r(vs * (1.f / 512.f)) + 1e-5f)));
#pragma unroll 1
            for (int h = 0; h < 2; h++) {
                const uint4 u = h ? u1 : u0;
                const uint32_t uu[4] = {u.x, u.y, u.z, u.w};
                uint32_t r[4];
#pragma unroll
                for (int i = 0; i < 4; i++)
                    r[i] = pack_bf16(__fdiv_rn(bf16r(bf_lo(uu[i]) - mb), den), __fdiv_rn(bf16r(bf_hi(uu[i]) - mb), den));
                *reinterpret_cast<uint4*>(sgen + SM_ACT + gw * ACT_PITCH + SEG_XN + h * 512 + lane * 16) = make_uint4(r[0], r[1], r[2], r[3]);
            }
        }
        bar_arrive(BAR_XN, 416);
        float wv[4] = {1.f, 1.f, 1.f, 1.f};
        const float* pa = g_mail + (hkv * 16 + gw * 4) * 512 + rhi * 128 + lane * 4;
        const float* pb = pa + 1024;
#pragma unroll 1
        for (int r = 0; r < 2; r++) {
            bar_sync(r ? BAR_VGO : BAR_QGO, 384);
            const uint32_t tag = reinterpret_cast<const uint32_t*>(sgen + SM_RED)[32];
            if (r == 0) mbar_wait(bar_full + QSLOT * 8, 0);
            {
                uint4 v[4];
                gather2x2(v, pa, pb, tag, 16 + r * 16 + gw * 4);
                const float o0 = fmaf(wv[0], __uint_as_float(v[0].x), wv[1] * __uint_as_float(v[1].x)) + fmaf(wv[2], __uint_as_float(v[2].x), wv[3] * __uint_as_float(v[3].x));
                const float o1 = fmaf(wv[0], __uint_as_float(v[0].y), wv[1] * __uint_as_float(v[1].y)) + fmaf(wv[2], __uint_as_float(v[2].y), wv[3] * __uint_as_float(v[3].y));
                const float o2 = fmaf(wv[0], __uint_as_float(v[0].z), wv[1] * __uint_as_float(v[1].z)) + fmaf(wv[2], __uint_as_float(v[2].z), wv[3] * __uint_as_float(v[3].z));
                const float o3 = fmaf(wv[0], __uint_as_float(v[0].w), wv[1] * __uint_as_float(v[1].w)) + fmaf(wv[2], __uint_as_float(v[2].w), wv[3] * __uint_as_float(v[3].w));
                *reinterpret_cast<uint2*>(sgen + SM_ACT + gw * ACT_PITCH + (r ? SEG_O : SEG_Q) + lane * 8) =
                    make_uint2(pack_bf16(o0, o1), pack_bf16(o2, o3));
                bar_arrive(r ? BAR_O : BAR_Q, 384);
            }
            if (r) break;
            bar_sync(BAR_SGO, 416);
            {
                const uint32_t side = reinterpret_cast<const uint32_t*>(sgen + SM_RED)[34];
                const int o = AR_O + slot_off(hkv * 16 + gw * 4) + rhi * 128 + lane * 4;
                pa = arena_base() + pick(o, side);
                pb = arena_base() + pick(o + 2048, side);
            }
            if (has_ffn) {
                const int rg = cta >> 2;
                uint4 v[4];
                gather<4>(v, g_mail + MAIL + ((rg >> 1) * 8 + (lane >> 4) * 4) * 512 + gw * 128 + (rg & 1) * 64 + (lane & 15) * 4, 512, tag);
                float h0 = 0.f, h1 = 0.f, h2 = 0.f, h3 = 0.f;
#pragma unroll
                for (int i = 0; i < 4; i++) {
                    h0 += __uint_as_float(v[i].x); h1 += __uint_as_float(v[i].y);
                    h2 += __uint_as_float(v[i].z); h3 += __uint_as_float(v[i].w);
                }
                h0 += __shfl_xor_sync(0xffffffffu, h0, 16); h1 += __shfl_xor_sync(0xffffffffu, h1, 16);
                h2 += __shfl_xor_sync(0xffffffffu, h2, 16); h3 += __shfl_xor_sync(0xffffffffu, h3, 16);
                if (lane < 16)
                    *reinterpret_cast<uint2*>(sgen + SM_ACT + gw * ACT_PITCH + SEG_H + lane * 8) =
                        make_uint2(pack_bf16(fmaxf(h0, 0.f), fmaxf(h1, 0.f)), pack_bf16(fmaxf(h2, 0.f), fmaxf(h3, 0.f)));
                bar_arrive(BAR_H, 384);
            }
            {
                uint4 v[1];
                gather<1>(v, g_xs + (hkv * 16 + gw * 4 + (lane & 3)) * 8 + (rhi >> 1) * 4, 0, tag);
                const float m = __uint_as_float(((rhi & 1) ? v[0].z : v[0].x) & ~3u);
                const float l = __uint_as_float((rhi & 1) ? v[0].w : v[0].y);
                float M = fmaxf(m, __shfl_xor_sync(0xffffffffu, m, 1));
                M = fmaxf(M, __shfl_xor_sync(0xffffffffu, M, 2));
                const float e = __expf(m - M);
                float L = e * l;
                L += __shfl_xor_sync(0xffffffffu, L, 1);
                L += __shfl_xor_sync(0xffffffffu, L, 2);
                const float wgt = e / L;
#pragma unroll
                for (int i = 0; i < 4; i++) wv[i] = __shfl_sync(0xffffffffu, wgt, i);
            }
        }
        PFLUSH(16 + gw * 4, 20 + gw * 4); PFLUSH(32 + gw * 4, 36 + gw * 4);
        return;
    }

    if (wix < 7) {
        const bool is_s = wix == 6;
        const int oidx = (lane >> 3) * 512 + cta * 4 + (lane & 3);
        const float xfin = __bfloat162float(x[oidx]);
        __nv_bfloat16* const optr = out + oidx;
        volatile uint32_t* gs = reinterpret_cast<volatile uint32_t*>(sgen + SM_RED);
        float* const ar = arena_base();
        uint32_t side;
        {
            float* pr = ar + pick(AR_PROBE + (cta >> 5) * 2048 + (cta & 31) * 32, is_s) + lane;
            put(pr, 0.f, 0u);
#pragma unroll 1
            for (int i = 0; i < NPROBE; i++) {
                bar_sync(BAR_PR, 64);
                if (lane == 0) {
                    uint32_t v, c;
                    asm volatile("atom.relaxed.gpu.global.add.u32 %0, [%1], 4;" : "=r"(v) : "l"(pr) : "memory");
                    asm volatile("{\n .reg .pred p;\n setp.ne.u32 p, %1, 1;\n mov.u32 %0, 0;\n @p mov.u32 %0, %%clock;\n}" : "=r"(c) : "r"(v));
                    gs[64 + 2 * i + is_s] = c;
                }
            }
            bar_sync(BAR_PR, 64);
            const bool s1 = lane < NPROBE && (int)(gs[64 + 2 * lane + 1] - gs[64 + 2 * lane]) < 0;
            const int votes = __popc(__ballot_sync(0xffffffffu, s1));
            side = votes > NPROBE / 2;
            if (is_s) { gs[34] = side; bar_arrive(BAR_SGO, 416); VSTAMP(56, 100 + (votes > NPROBE / 2 ? votes : NPROBE - votes)); DSTAMP(57, side); }
        }
        const int p = lane >> 2;
        const int o = (is_s ? AR_S : AR_F) + slot_off(p * 4 + (cta >> 5)) + (cta & 31) * 16 + (lane & 3) * 4;
        const bool skip3 = !is_s && p >= 4;
        const float* s0 = ar + pick(o, side);
        const float* s1 = ar + pick(o + 32768, side);
        const float* s2 = ar + pick(o + 65536, side);
        const float* s3 = skip3 ? s0 : ar + pick(o + 98304, side);
        const bool u16 = lane & 16, u8 = lane & 8;
        if (is_s) gs[lane] = 0xffffffffu;
        bar_sync(BAR_FGO, 320);
        if (is_s) bar_sync(BAR_SREL, 288);
        const uint32_t tag = gs[32];
        DSTAMP(is_s ? 48 : 52, tag);
        uint4 v0 = ld_v4(s0), v1 = ld_v4(s1), v2 = ld_v4(s2), v3 = ld_v4(s3);
        unsigned it = 0;
        uint32_t gate;
        while (true) {
            const bool k0 = tag_ok(v0, tag), k1 = tag_ok(v1, tag), k2 = tag_ok(v2, tag), k3 = tag_ok(v3, tag);
            asm volatile("ld.volatile.shared.u32 %0, [%1];" : "=r"(gate) : "r"(sbase + SM_RED + lane * 4 + (v3.x & 0u) + (k0 ? 0u : 0u)) : "memory");
            if (__all_sync(0xffffffffu, k0 && k1 && k2 && k3 && (!is_s || gate != 0xffffffffu))) break;
            if (!k0) v0 = ld_v4(s0);
            if (!k1) v1 = ld_v4(s1);
            if (!k2) v2 = ld_v4(s2);
            if (!k3) v3 = ld_v4(s3);
            if (++it > SPIN_LIMIT) __trap();
        }
        DSTAMP(is_s ? 50 : 54, v0.x ^ v3.x); VSTAMP(is_s ? 51 : 55, it + 1);
        if (skip3) v3 = make_uint4(0u, 0u, 0u, 0u);
        const float a0 = (__uint_as_float(v0.x) + __uint_as_float(v1.x)) + (__uint_as_float(v2.x) + __uint_as_float(v3.x));
        const float a1 = (__uint_as_float(v0.y) + __uint_as_float(v1.y)) + (__uint_as_float(v2.y) + __uint_as_float(v3.y));
        const float a2 = (__uint_as_float(v0.z) + __uint_as_float(v1.z)) + (__uint_as_float(v2.z) + __uint_as_float(v3.z));
        const float a3 = (__uint_as_float(v0.w) + __uint_as_float(v1.w)) + (__uint_as_float(v2.w) + __uint_as_float(v3.w));
        const float b0 = (u16 ? a2 : a0) + __shfl_xor_sync(0xffffffffu, u16 ? a0 : a2, 16);
        const float b1 = (u16 ? a3 : a1) + __shfl_xor_sync(0xffffffffu, u16 ? a1 : a3, 16);
        float c = (u8 ? b1 : b0) + __shfl_xor_sync(0xffffffffu, u8 ? b0 : b1, 8);
        c += __shfl_xor_sync(0xffffffffu, c, 4);
        const float tot = bf16r(c);
        if (is_s) {
            if (!(lane & 4)) *optr = __float2bfloat16_rn(xfin + bf16r(tot * __uint_as_float(gate)));
            if (cta == 0 && lane == 0) g_epoch = (tag == 3) ? 0u : tag;
            DSTAMP(11, __float_as_uint(tot));
            PFLUSH(11, 12); PFLUSH(56, 58);
        } else {
            gs[lane] = __float_as_uint(bf16r(__fdividef(tot, 1.f + __expf(-tot))));
        }
        PFLUSH(is_s ? 48 : 52, is_s ? 52 : 56);
        return;
    }

    const int tid = tix - 224, warp = wix - 7;
    unsigned epoch;
    asm volatile("ld.relaxed.gpu.global.u32 %0, [%1];" : "=r"(epoch) : "l"(&g_epoch) : "memory");
    {
        clear4(g_mail + (tid >> 7) * MAIL + cta * 512 + (tid & 127) * 4);
        float* mb = arena_base() + slot_off(cta) + (tid >> 7) * 1024 + (tid & 127) * 4;
        clear4(mb + AR_O);
        clear4(mb + AR_F);
        clear4(mb + AR_S);
        if (tid < 2) clear4(g_xs + cta * 8 + tid * 4);
    }
    const int g = lane >> 2, t = lane & 3;
    Ring ring{bar_full, bar_empty, 0, 0u};
    const int lrow = lane & 7, lmat = lane >> 3;
    const uint32_t a_off = sbase + (warp >> 2) * 8192 + (lrow + ((lmat >> 1) << 3)) * 128 + ((((warp & 3) * 2 + (lmat & 1)) ^ lrow) << 4);
    const uint32_t b_off = sbase + SM_ACT + (lane & 3) * ACT_PITCH + lmat * 16;
    const int pofs = (t & 1) * 256 + warp * 16 + g + (t >> 1) * 8;
    float* const pub2 = arena_base() + slot_off(cta) + (warp * 16 + g + (t >> 1) * 8) * 4 + (t & 1) * 2;
    const bool hi = t >= 2;
    bar_sync(BAR_XN, 416);
    const uint32_t tag = epoch + 1;
    if (tid == 0) { reinterpret_cast<uint32_t*>(sgen + SM_RED)[32] = tag; }
    CSTAMP(2);

#pragma unroll 1
    for (int ph = 0; ph < 4; ph++) {
        if ((ph & 1) && !has_ffn) continue;
        if (ph == 2) {
            bar_sync(BAR_Q, 384);
            CSTAMP(4);
            uint32_t qa[16];
            const uint8_t* qs = sgen + SM_ACT + (g & 3) * ACT_PITCH + SEG_Q + t * 4;
#pragma unroll
            for (int k = 0; k < 16; k++) qa[k] = *reinterpret_cast<const uint32_t*>(qs + k * 16);
            const uint32_t k_off = sbase + (warp * 8 + lrow) * 128;
            const uint32_t sw0 = ((lmat) ^ lrow) << 4, sw1 = ((lmat + 4) ^ lrow) << 4;
            float mx = -INFINITY;
            uint8_t* sdst = sgen + SM_ACT + g * ACT_PITCH + SEG_P + (warp * 8 + 2 * t) * 2;
#pragma unroll 1
            for (int it = 0; it < KT; it++) {
                ring.wait();
                const uint32_t tb = ring.slot * TILE_B + k_off;
                uint32_t b[16];
                ldsm4(tb + sw0, b[0], b[1], b[2], b[3]);
                ldsm4(tb + sw1, b[4], b[5], b[6], b[7]);
                ldsm4(tb + 8192 + sw0, b[8], b[9], b[10], b[11]);
                ldsm4(tb + 8192 + sw1, b[12], b[13], b[14], b[15]);
                float c0[4] = {0.f, 0.f, 0.f, 0.f}, c1[4] = {0.f, 0.f, 0.f, 0.f};
#pragma unroll
                for (int k = 0; k < 8; k += 2) {
                    mma16816(c0, qa[2 * k], 0u, qa[2 * k + 1], 0u, b[2 * k], b[2 * k + 1]);
                    mma16816(c1, qa[2 * k + 2], 0u, qa[2 * k + 3], 0u, b[2 * k + 2], b[2 * k + 3]);
                }
                ring.release(lane);
                const float scale = 0.08838834764831845f;
                const uint32_t sp = pack_bf16(bf16r(c0[0] + c1[0]) * scale, bf16r(c0[1] + c1[1]) * scale);
                mx = fmaxf(mx, fmaxf(bf_lo(sp), bf_hi(sp)));
                if (lane < 16) *reinterpret_cast<uint32_t*>(sdst + it * 128) = sp;
            }
            mx = fmaxf(mx, __shfl_xor_sync(0xffffffffu, mx, 1));
            mx = fmaxf(mx, __shfl_xor_sync(0xffffffffu, mx, 2));
            if (lane < 16 && t == 0) reinterpret_cast<float*>(sgen + SM_WMAX)[warp * 4 + g] = mx;
            bar_sync(BAR_MMA, 256);
            CSTAMP(5);
            const int head = warp >> 1;
            const float* wm = reinterpret_cast<const float*>(sgen + SM_WMAX) + head;
            float m = wm[0];
#pragma unroll
            for (int i = 1; i < 8; i++) m = fmaxf(m, wm[4 * i]);
            const float L2E = 1.4426950408889634f;
            const float mb = m * L2E;
            uint8_t* pp = sgen + SM_ACT + head * ACT_PITCH + SEG_P + (warp & 1) * 1024 + lane * 16;
            float l = 0.f;
#pragma unroll 1
            for (int h = 0; h < 2; h++) {
                uint4 u = *reinterpret_cast<const uint4*>(pp + h * 512);
                uint32_t w[4] = {u.x, u.y, u.z, u.w};
#pragma unroll
                for (int i = 0; i < 4; i++) {
                    const float p0 = exp2f(fmaf(bf_lo(w[i]), L2E, -mb)), p1 = exp2f(fmaf(bf_hi(w[i]), L2E, -mb));
                    l += p0 + p1;
                    w[i] = pack_bf16(p0, p1);
                }
                *reinterpret_cast<uint4*>(pp + h * 512) = make_uint4(w[0], w[1], w[2], w[3]);
            }
#pragma unroll
            for (int o = 16; o; o >>= 1) l += __shfl_xor_sync(0xffffffffu, l, o);
            if (lane == 0) reinterpret_cast<float*>(sgen + SM_LSUM)[warp] = l;
            bar_sync(BAR_MMA, 256);
            if ((warp & 1) && lane < 2) {
                const float* ls = reinterpret_cast<const float*>(sgen + SM_LSUM);
                put(g_xs + cta * 8 + head * 2 + lane, lane ? ls[warp - 1] + ls[warp] : m, tag);
            }
            CSTAMP(6);
        }
        const int n = (ph == 2) ? KT : ((ph & 1) ? 1 : 2);
        const int seg = (ph == 0) ? SEG_XN + rlo * 256 : (ph == 1) ? SEG_XN + (cta & 7) * 128 : (ph == 2) ? SEG_P : SEG_H;
        uint32_t ba = b_off + seg;
        float c0[4] = {0.f, 0.f, 0.f, 0.f}, c1[4] = {0.f, 0.f, 0.f, 0.f};
        if (ph == 3) bar_sync(BAR_H, 384);
#pragma unroll 1
        for (int i = 0; i < n; i++) {
            if (i == SGO) bar_arrive(BAR_SGO, 416);
            if (i == VGO) bar_arrive(BAR_VGO, 384);
            uint32_t a[16], b[8];
            ldsm4(ba, b[0], b[1], b[2], b[3]);
            ldsm4(ba + 64, b[4], b[5], b[6], b[7]);
            ring.wait();
            const uint32_t aa = a_off + ring.slot * TILE_B;
#pragma unroll
            for (int k = 0; k < 4; k++) ldsm4t(aa + k * 2048, a[4 * k], a[4 * k + 1], a[4 * k + 2], a[4 * k + 3]);
            mma16816(c0, a[0], a[1], a[2], a[3], b[0], b[1]);
            mma16816(c1, a[4], a[5], a[6], a[7], b[2], b[3]);
            mma16816(c0, a[8], a[9], a[10], a[11], b[4], b[5]);
            mma16816(c1, a[12], a[13], a[14], a[15], b[6], b[7]);
            ring.release(lane);
            ba += 128;
        }
        {
            const float r0 = hi ? c0[2] + c1[2] : c0[0] + c1[0], r1 = hi ? c0[3] + c1[3] : c0[1] + c1[1];
            if (ph == 3) { put2(pub2 + AR_F, r0, r1, tag); put2(pub2 + AR_F + 1024, r0, r1, tag); }
            else {
                float* pd = (ph == 2 ? arena_base() + AR_O + slot_off(cta) : g_mail + ph * MAIL + cta * 512) + pofs;
                put(pd, r0, tag); put(pd + 128, r1, tag);
                if (ph == 2) { put(pd + 1024, r0, tag); put(pd + 1152, r1, tag); }
            }
        }
        if (ph == 0) bar_arrive(BAR_QGO, 384);
        if (ph == 2) {
            if (VGO == 99) bar_arrive(BAR_VGO, 384);
        }
    }
    if (FGO == 0) bar_arrive(BAR_FGO, 320);
    {
        uint32_t a[16], b[16];
        float c[4][4];
#pragma unroll
        for (int k = 0; k < 4; k++) { c[k][0] = 0.f; c[k][1] = 0.f; c[k][2] = 0.f; c[k][3] = 0.f; }
#pragma unroll
        for (int i = 0; i < 2; i++) {
            if (VGO == 16 && i == 0) bar_arrive(BAR_VGO, 384);
            ring.wait();
            if (VGO == 17 + i) bar_arrive(BAR_VGO, 384);
            if (FGO == 1 + i) bar_arrive(BAR_FGO, 320);
            if (SREL == 1 + i) bar_arrive(BAR_SREL, 288);
            const uint32_t aa = a_off + ring.slot * TILE_B;
#pragma unroll
            for (int k = 0; k < 4; k++) ldsm4t(aa + k * 2048, a[4 * k], a[4 * k + 1], a[4 * k + 2], a[4 * k + 3]);
            if (++ring.slot == NSLOT) { ring.slot = 0; ring.phase ^= 1; }
            if (i == 0) {
                bar_sync(BAR_O, 384);
#pragma unroll
                for (int k = 0; k < 4; k++) ldsm4(b_off + SEG_O + k * 64, b[4 * k], b[4 * k + 1], b[4 * k + 2], b[4 * k + 3]);
            }
#pragma unroll
            for (int k = 0; k < 4; k++) mma16816(c[k], a[4 * k], a[4 * k + 1], a[4 * k + 2], a[4 * k + 3], b[8 * i + 2 * k], b[8 * i + 2 * k + 1]);
        }
        float r0, r1;
        if (hi) { r0 = (c[0][2] + c[1][2]) + (c[2][2] + c[3][2]); r1 = (c[0][3] + c[1][3]) + (c[2][3] + c[3][3]); }
        else    { r0 = (c[0][0] + c[1][0]) + (c[2][0] + c[3][0]); r1 = (c[0][1] + c[1][1]) + (c[2][1] + c[3][1]); }
        put2(pub2 + AR_S, r0, r1, tag);
        put2(pub2 + AR_S + 1024, r0, r1, tag);
        if (SREL == 3) bar_arrive(BAR_SREL, 288);
    }
}

typedef CUresult (*EncodeFn)(CUtensorMap*, CUtensorMapDataType, cuuint32_t, void*, const cuuint64_t*, const cuuint64_t*,
                             const cuuint32_t*, const cuuint32_t*, CUtensorMapInterleave, CUtensorMapSwizzle,
                             CUtensorMapL2promotion, CUtensorMapFloatOOBfill);

void make_map(EncodeFn enc, CUtensorMap* m, const void* base, uint64_t rows, uint64_t cols) {
    cuuint64_t dims[3] = {64, rows, cols / 64};
    cuuint64_t strides[2] = {cols * 2, 128};
    cuuint32_t box[3] = {64, 64, 2};
    cuuint32_t es[3] = {1, 1, 1};
    enc(m, CU_TENSOR_MAP_DATA_TYPE_BFLOAT16, 3, const_cast<void*>(base), dims, strides, box, es,
        CU_TENSOR_MAP_INTERLEAVE_NONE, CU_TENSOR_MAP_SWIZZLE_128B, CU_TENSOR_MAP_L2_PROMOTION_L2_256B,
        CU_TENSOR_MAP_FLOAT_OOB_FILL_NONE);
}

}

extern "C" void kernel_launch(void* const* d_in, const int* in_sizes, int n_in, void* d_out, int out_size) {
    (void)in_sizes; (void)n_in; (void)out_size;
    static EncodeFn enc = nullptr;
    if (!enc) {
        void* fn = nullptr;
        cudaDriverEntryPointQueryResult qr;
        cudaGetDriverEntryPoint("cuTensorMapEncodeTiled", &fn, cudaEnableDefault, &qr);
        enc = (EncodeFn)fn;
        cudaFuncSetAttribute(fused_decode_kernel, cudaFuncAttributeMaxDynamicSharedMemorySize, SM_TOTAL + 1024);
    }
    Maps maps;
    make_map(enc, &maps.m[0], d_in[3], 512, 4096);
    make_map(enc, &maps.m[1], d_in[6], 512, 1792);
    make_map(enc, &maps.m[2], d_in[1], 4ull * 8 * 16384, 128);
    make_map(enc, &maps.m[3], d_in[2], 4ull * 8 * 16384, 128);
    make_map(enc, &maps.m[4], d_in[7], 1792, 512);
    make_map(enc, &maps.m[5], d_in[4], 4096, 512);
#define LTHREADS NTHREADS
    fused_decode_kernel<<<NCTA, LTHREADS, SM_TOTAL + 1024>>>(maps, (const __nv_bfloat16*)d_in[0], (__nv_bfloat16*)d_out);
}
```

```cpp
#include <cuda_runtime.h>
#include <cuda_bf16.h>
#include <cuda.h>
#include <stdint.h>

#define TAU 658
#define LEADF 22
#define INFLIGHT 8
#define TAILJ 32
#define TAILD 3
#define ADV 0
#define SQ 0
#define SELP
#define DEPV bad
#define SPREAD 1
#define WOSPIN
#define PHI (((cta >> 2) * 13) & 31)
#define PROMO CU_TENSOR_MAP_L2_PROMOTION_L2_256B
#define NPC 2
#define NSPT 2
#define NXB (NSPT * (NPC - 1))
#define REMAP 0
#define CLRMODE 0
#define TMAPOL 0x12F0000000000000ull
#define CLRO 12
#define CLRF 13
#define CLRS 14
#define W1POS 8
#define QSLOT 5
#define SGO 12
#define NPROBE 4

namespace {

constexpr int NCTA     = 128;
constexpr int NFFN     = 112;
constexpr int NSLOT    = 13;
constexpr int TILE_B   = 16384;
#define NS 3
#define SSTAG 150
constexpr int NTHREADS = 448 + 32 * NS;
constexpr int NSGO     = 416 + 32 * NS;
constexpr int KT       = 16;

constexpr int SEG_XN = 0;
constexpr int SEG_P  = 1024;
constexpr int SEG_H  = 3072;
constexpr int SEG_O  = 3200;
constexpr int SEG_Q  = 3456;
constexpr int ACT_PITCH = 3712 + 16;
constexpr int SM_ACT   = NSLOT * TILE_B;
constexpr int SM_WMAX  = SM_ACT + 4 * ACT_PITCH;
constexpr int SM_LSUM  = SM_WMAX + 128;
constexpr int SM_MISC  = SM_LSUM + 32;
constexpr int SM_BAR   = SM_MISC + 512;
constexpr int SM_TOTAL = SM_BAR + 2 * NSLOT * 8 + 64;
static_assert(SM_TOTAL + 1024 + 256 <= 232448, "smem");

constexpr int BAR_MMA = 1, BAR_XN = 2, BAR_Q = 3, BAR_H = 4, BAR_O = 5, BAR_VGO = 6, BAR_QGO = 7, BAR_SGO = 8,
              BAR_FGO = 9, BAR_SREL = 10;

#define ARENA_MB 4
__device__ __align__(4096) float g_arena[ARENA_MB << 18];
constexpr int AR_O = 0, AR_F = 131072, AR_S = 262144, AR_Q = 393216, MAIL = NCTA * 512;
constexpr int AR_XS = AR_F + (NFFN / 2) * 2048;
constexpr int AR_EPOCH = AR_XS + 2048;
constexpr uint32_t HOME_MASK = (1u << 12) | (1u << 13) | (1u << 16) | (1u << 17) | (1u << 19);

struct Params {
    CUtensorMap m[7];
    const char* raw[3];
    const __nv_bfloat16* x;
    __nv_bfloat16* out;
    float* arena;
};

#define DSTAMP(i, dep) do {} while (0)
#define MSTAMP(i, dep) do {} while (0)
#define VSTAMP(i, val) do {} while (0)
#define PFLUSH(lo, hi) do {} while (0)

constexpr unsigned SPIN_LIMIT = 1u << 20;

__device__ __forceinline__ int slot_off(int producer) { return (producer >> 1) * 2048 + (producer & 1) * 512; }
__device__ __forceinline__ int pick(int off, uint32_t side) {
    return off + (((__popc(((uint32_t)off << 2) & HOME_MASK) ^ side) & 1) << 10);
}

__device__ __forceinline__ void mbar_init(uint32_t bar, uint32_t cnt) {
    asm volatile("mbarrier.init.shared::cta.b64 [%0], %1;" :: "r"(bar), "r"(cnt) : "memory");
}
__device__ __forceinline__ void mbar_expect_tx(uint32_t bar, uint32_t bytes) {
    asm volatile("mbarrier.arrive.expect_tx.shared::cta.b64 _, [%0], %1;" :: "r"(bar), "r"(bytes) : "memory");
}
__device__ __forceinline__ void mbar_arrive(uint32_t bar) {
    asm volatile("mbarrier.arrive.shared::cta.b64 _, [%0];" :: "r"(bar) : "memory");
}
__device__ __forceinline__ void mbar_wait(uint32_t bar, uint32_t parity) {
    uint32_t ok, it = 0;
    do {
        asm volatile("{\n .reg .pred p;\n mbarrier.try_wait.parity.shared::cta.b64 p, [%1], %2, %3;\n selp.u32 %0, 1, 0, p;\n}"
                     : "=r"(ok) : "r"(bar), "r"(parity), "r"(10000) : "memory");
        if (ok) break;
        if (++it > SPIN_LIMIT) __trap();
    } while (true);
}
__device__ __forceinline__ void mbar_spin(uint32_t bar, uint32_t parity) {
    uint32_t ok, it = 0;
    do {
        asm volatile("{\n .reg .pred p;\n mbarrier.try_wait.parity.shared::cta.b64 p, [%1], %2;\n selp.u32 %0, 1, 0, p;\n}"
                     : "=r"(ok) : "r"(bar), "r"(parity) : "memory");
        if (ok) break;
        if (++it > 16 * SPIN_LIMIT) __trap();
    } while (true);
}
__device__ __forceinline__ void tma_tile(uint32_t dst, const CUtensorMap* tm, int row, int half, uint32_t bar) {
    asm volatile("cp.async.bulk.tensor.3d.shared::cluster.global.mbarrier::complete_tx::bytes.L2::cache_hint [%0], [%1, {%3, %4, %5}], [%2], %6;"
                 :: "r"(dst), "l"(tm), "r"(bar), "r"(0), "r"(row), "r"(half), "l"(TMAPOL) : "memory");
}
__device__ __forceinline__ void ldsm4(uint32_t addr, uint32_t& r0, uint32_t& r1, uint32_t& r2, uint32_t& r3) {
    asm volatile("ldmatrix.sync.aligned.m8n8.x4.shared.b16 {%0,%1,%2,%3}, [%4];"
                 : "=r"(r0), "=r"(r1), "=r"(r2), "=r"(r3) : "r"(addr) : "memory");
}
__device__ __forceinline__ void ldsm4t(uint32_t addr, uint32_t& r0, uint32_t& r1, uint32_t& r2, uint32_t& r3) {
    asm volatile("ldmatrix.sync.aligned.m8n8.x4.trans.shared.b16 {%0,%1,%2,%3}, [%4];"
                 : "=r"(r0), "=r"(r1), "=r"(r2), "=r"(r3) : "r"(addr) : "memory");
}
__device__ __forceinline__ void mma16816(float (&c)[4], uint32_t a0, uint32_t a1, uint32_t a2, uint32_t a3,
                                         uint32_t b0, uint32_t b1) {
    asm volatile("mma.sync.aligned.m16n8k16.row.col.f32.bf16.bf16.f32 {%0,%1,%2,%3}, {%4,%5,%6,%7}, {%8,%9}, {%0,%1,%2,%3};"
                 : "+f"(c[0]), "+f"(c[1]), "+f"(c[2]), "+f"(c[3])
                 : "r"(a0), "r"(a1), "r"(a2), "r"(a3), "r"(b0), "r"(b1));
}
__device__ __forceinline__ void bar_sync(int id, int n) { asm volatile("bar.sync %0, %1;" :: "r"(id), "r"(n) : "memory"); }
__device__ __forceinline__ void bar_arrive(int id, int n) { asm volatile("bar.arrive %0, %1;" :: "r"(id), "r"(n) : "memory"); }
__device__ __forceinline__ unsigned gtime32() { unsigned t; asm volatile("mov.u32 %0, %globaltimer_lo;" : "=r"(t)); return t; }

__device__ __forceinline__ float bf16r(float v) {
    uint32_t d; asm("cvt.rn.bf16x2.f32 %0, %1, %2;" : "=r"(d) : "f"(v), "f"(0.f));
    return __uint_as_float(d);
}
__device__ __forceinline__ uint32_t pack_bf16(float lo, float hi) {
    uint32_t d; asm("cvt.rn.bf16x2.f32 %0, %1, %2;" : "=r"(d) : "f"(hi), "f"(lo));
    return d;
}
__device__ __forceinline__ float bf_lo(uint32_t u) { return __uint_as_float(u << 16); }
__device__ __forceinline__ float bf_hi(uint32_t u) { return __uint_as_float(u & 0xffff0000u); }
__device__ __forceinline__ float asf(uint32_t u) { return __uint_as_float(u); }

__device__ __forceinline__ uint32_t tagged(float v, uint32_t tag) { return (__float_as_uint(v) & ~3u) | tag; }
__device__ __forceinline__ void st1(float* p, uint32_t u) {
    asm volatile("st.relaxed.gpu.global.u32 [%0], %1;" :: "l"(p), "r"(u) : "memory");
}
__device__ __forceinline__ void st2(float* p, uint32_t u0, uint32_t u1) {
    asm volatile("st.relaxed.gpu.global.v2.u32 [%0], {%1, %2};" :: "l"(p), "r"(u0), "r"(u1) : "memory");
}
__device__ __forceinline__ void clear4(float* p) {
    asm volatile("st.relaxed.gpu.global.v4.u32 [%0], {%1,%1,%1,%1};" :: "l"(p), "r"(0u) : "memory");
}
__device__ __forceinline__ uint4 ld4(const float* p) {
    uint4 v;
    asm volatile("ld.relaxed.gpu.global.v4.u32 {%0,%1,%2,%3}, [%4];" : "=r"(v.x), "=r"(v.y), "=r"(v.z), "=r"(v.w) : "l"(p) : "memory");
    return v;
}
__device__ __forceinline__ uint32_t badbits(const uint4& v, uint32_t tag) {
    uint32_t a, b;
    asm("lop3.b32 %0, %1, %2, %3, 0x7e;" : "=r"(a) : "r"(v.x), "r"(tag), "r"(v.y));
    asm("lop3.b32 %0, %1, %2, %3, 0x7e;" : "=r"(b) : "r"(v.z), "r"(tag), "r"(v.w));
    return a | b;
}
__device__ __forceinline__ uint32_t neq2(uint32_t x, uint32_t y, uint32_t tag) {
    uint32_t a; asm("lop3.b32 %0, %1, %2, %3, 0x7e;" : "=r"(a) : "r"(x), "r"(tag), "r"(y)); return a;
}
__device__ __forceinline__ uint32_t or3(uint32_t x, uint32_t y, uint32_t z) {
    uint32_t a; asm("lop3.b32 %0, %1, %2, %3, 0xfe;" : "=r"(a) : "r"(x), "r"(y), "r"(z)); return a;
}
__device__ __forceinline__ void gather4(uint4 (&v)[4], const float* p0, const float* p1, const float* p2, const float* p3, uint32_t tag, int which = 0) {
    v[0] = ld4(p0); v[1] = ld4(p1); v[2] = ld4(p2); v[3] = ld4(p3);
    unsigned it = 0;
    while (true) {
        const uint32_t b0 = badbits(v[0], tag), b1 = badbits(v[1], tag), b2 = badbits(v[2], tag), b3 = badbits(v[3], tag);
        if (!__any_sync(0xffffffffu, ((b0 | b1) | (b2 | b3)) & 3u)) break;
        if (b0 & 3u) v[0] = ld4(p0);
        if (b1 & 3u) v[1] = ld4(p1);
        if (b2 & 3u) v[2] = ld4(p2);
        if (b3 & 3u) v[3] = ld4(p3);
        if (++it > SPIN_LIMIT) __trap();
    }
}
__device__ __forceinline__ float reduce32(const uint4 (&v)[4], bool u16, bool u8) {
    const float a0 = (asf(v[0].x) + asf(v[1].x)) + (asf(v[2].x) + asf(v[3].x));
    const float a1 = (asf(v[0].y) + asf(v[1].y)) + (asf(v[2].y) + asf(v[3].y));
    const float a2 = (asf(v[0].z) + asf(v[1].z)) + (asf(v[2].z) + asf(v[3].z));
    const float a3 = (asf(v[0].w) + asf(v[1].w)) + (asf(v[2].w) + asf(v[3].w));
    const float b0 = (u16 ? a2 : a0) + __shfl_xor_sync(0xffffffffu, u16 ? a0 : a2, 16);
    const float b1 = (u16 ? a3 : a1) + __shfl_xor_sync(0xffffffffu, u16 ? a1 : a3, 16);
    float c = (u8 ? b1 : b0) + __shfl_xor_sync(0xffffffffu, u8 ? b0 : b1, 8);
    c += __shfl_xor_sync(0xffffffffu, c, 4);
    return c;
}

__device__ __forceinline__ uint32_t near_side(volatile uint32_t* misc) {
    int votes = 0, diff = 0;
#pragma unroll
    for (int i = 0; i < 4; i++) {
        const int d = (int)(misc[64 + 2 * i] - misc[65 + 2 * i]);
        votes += d > 0 ? 1 : -1; diff += d;
    }
    return votes ? votes > 0 : diff > 0;
}

struct Ring {
    uint32_t full, empty;
    int slot; uint32_t phase;
    __device__ __forceinline__ void wait() { mbar_wait(full + slot * 8, phase); }
    __device__ __forceinline__ void next() { if (++slot == NSLOT) { slot = 0; phase ^= 1; } }
    __device__ __forceinline__ void release(int lane) {
        __syncwarp();
        if (lane == 0) mbar_arrive(empty + slot * 8);
        next();
    }
};

__global__ void __launch_bounds__(NTHREADS, 1)
fused_decode_kernel(const __grid_constant__ Params prm) {
    extern __shared__ uint8_t smem_raw[];
    const uint32_t sbase = ((uint32_t)__cvta_generic_to_shared(smem_raw) + 1023u) & ~1023u;
    uint8_t* sgen = smem_raw + (sbase - (uint32_t)__cvta_generic_to_shared(smem_raw));
    const int cta = blockIdx.x;
    const int hkv = cta >> 4, rhi = (cta >> 2) & 3, rlo = cta & 3;
    const bool has_ffn = cta < NFFN;
    const uint32_t bar_full = sbase + SM_BAR, bar_empty = bar_full + NSLOT * 8;

    if (threadIdx.x - 1u < 31u) return;
    if (threadIdx.x == 0) {
        const unsigned t0 = gtime32();
        DSTAMP(0, 0);
        mbar_init(bar_full, 1);
        asm volatile("fence.mbarrier_init.release.cluster;" ::: "memory");
        mbar_expect_tx(bar_full, TILE_B);
        tma_tile(sbase, &prm.m[0], rlo * 128, (cta >> 2) * 2, bar_full);
#pragma unroll
        for (int i = 1; i < 2 * NSLOT + NXB; i++) mbar_init(bar_full + i * 8, (i < NSLOT || i >= 2 * NSLOT) ? 1 : 8);
        asm volatile("fence.mbarrier_init.release.cluster;" ::: "memory");
        asm volatile("barrier.arrive %0, %1;" :: "n"(BAR_XN), "n"(448) : "memory");
        const int kvrow = (rhi * 8 + hkv) * 16384 + 12288 + rlo * 64;
        const int toff = ((PHI) * TAU) / 32 - (LEADF * TAU) / 16;
        constexpr int P_W1 = 18 + W1POS, P_W2 = 35, P_END = 38;
        int slot = 1; uint32_t eph = 1;
        int fslot = 0; uint32_t fph = 0;
        int landed = 0, total = 1;
#pragma unroll 1
        for (int v = 1; v < P_END; v++) {
            int mi, row, half;
            if (v == 1)          { mi = 0; row = rlo * 128 + 64; half = (cta >> 2) * 2; }
            else if (v == P_W1)  { mi = 1; row = (cta & 7) * 64; half = (cta >> 3) * 2; }
            else if (v < P_W2)   { const int j = v - 2 - (v > P_W1); mi = 2 + (j >> 4); row = kvrow + (j & 15) * 256; half = 0; }
            else if (v == P_W2)  { mi = 4; row = (cta >> 2) * 64; half = rlo * 2; }
            else                 { mi = 5; row = (cta >> 2) * 128 + (v - P_W2 - 1) * 64; half = rlo * 2; }
            if (v < 7) asm volatile("prefetch.tensormap [%0];" :: "l"(&prm.m[v]) : "memory");
            if (v == 10) asm volatile("cp.async.bulk.prefetch.L2.global [%0], 128;" :: "l"(prm.raw[0] + (size_t)kvrow * 256) : "memory");
            if (v == 27) {
                if (has_ffn) asm volatile("cp.async.bulk.prefetch.L2.global [%0], 128;" :: "l"(prm.raw[1] + (cta >> 2) * 65536 + rlo * 256) : "memory");
                asm volatile("cp.async.bulk.prefetch.L2.global [%0], 128;" :: "l"(prm.raw[2] + (cta >> 2) * 131072 + rlo * 256) : "memory");
            }
            if (!has_ffn && (v == P_W1 || v == P_W2)) continue;
            const int need = total + 1 - (v >= TAILJ + 3 ? TAILD : INFLIGHT);
            while (landed < need) {
                mbar_wait(bar_full + fslot * 8, fph);
                if (++fslot == NSLOT) { fslot = 0; fph ^= 1; }
                landed++;
            }
            if (total >= NSLOT) mbar_wait(bar_empty + slot * 8, eph);
            const int due = (v - (!has_ffn && v > P_W2)) * TAU + toff;
            while ((int)(gtime32() - t0) < due) {}
            if (NPC > 1 && v >= P_END - NSPT) {
#pragma unroll
                for (int q = 0; q < NPC; q++) {
                    const uint32_t bq = q ? bar_full + (2 * NSLOT + (v - (P_END - NSPT)) * (NPC - 1) + q - 1) * 8 : bar_full + slot * 8;
                    mbar_expect_tx(bq, TILE_B / NPC);
                    tma_tile(sbase + slot * TILE_B + q * (TILE_B / NPC), &prm.m[6], row + q * (64 / NPC), half, bq);
                }
            } else {
                mbar_expect_tx(bar_full + slot * 8, TILE_B);
                tma_tile(sbase + slot * TILE_B, &prm.m[mi], row, half, bar_full + slot * 8);
            }
            if (++slot == NSLOT) { slot = 0; eph ^= 1; }
            total++;
        }
        DSTAMP(1, 0);
    }
    int tix;
    asm volatile("mov.u32 %0, %%tid.x;" : "=r"(tix));
    if (tix == 0) return;
    const int lane = tix & 31;
    const int wix = __shfl_sync(0xffffffffu, tix >> 5, 0);
    volatile uint32_t* misc = reinterpret_cast<volatile uint32_t*>(sgen + SM_MISC);

    if (wix < 5) {
        const int gw = wix - 1;
        {
            const uint4* xr = reinterpret_cast<const uint4*>(prm.x + gw * 512);
            const uint4 u0 = __ldg(xr + lane), u1 = __ldg(xr + 32 + lane);
            const uint32_t w[8] = {u0.x, u0.y, u0.z, u0.w, u1.x, u1.y, u1.z, u1.w};
            float s = 0.f;
#pragma unroll
            for (int i = 0; i < 8; i++) s += bf_lo(w[i]) + bf_hi(w[i]);
#pragma unroll
            for (int o = 16; o; o >>= 1) s += __shfl_xor_sync(0xffffffffu, s, o);
            const float mean = s * (1.f / 512.f);
            float vs = 0.f;
#pragma unroll
            for (int i = 0; i < 8; i++) { const float d0 = bf_lo(w[i]) - mean, d1 = bf_hi(w[i]) - mean; vs += d0 * d0 + d1 * d1; }
#pragma unroll
            for (int o = 16; o; o >>= 1) vs += __shfl_xor_sync(0xffffffffu, vs, o);
            const float mb = bf16r(mean);
            const float den = bf16r(sqrtf(bf16r(bf16r(vs * (1.f / 512.f)) + 1e-5f)));
#pragma unroll 1
            for (int h = 0; h < 2; h++) {
                const uint4 u = h ? u1 : u0;
                const uint32_t uu[4] = {u.x, u.y, u.z, u.w};
                uint32_t r[4];
#pragma unroll
                for (int i = 0; i < 4; i++)
                    r[i] = pack_bf16(__fdiv_rn(bf16r(bf_lo(uu[i]) - mb), den), __fdiv_rn(bf16r(bf_hi(uu[i]) - mb), den));
                *reinterpret_cast<uint4*>(sgen + SM_ACT + gw * ACT_PITCH + SEG_XN + h * 512 + lane * 16) = make_uint4(r[0], r[1], r[2], r[3]);
            }
        }
        bar_arrive(BAR_XN, 448);
        float wv[4] = {1.f, 1.f, 1.f, 1.f};
        const float* pa = prm.arena + AR_Q + (hkv * 16 + gw * 4) * 512 + rhi * 128 + lane * 4;
        const float* pb = pa + 1024;
#pragma unroll 1
        for (int r = 0; r < 2; r++) {
            bar_sync(r ? BAR_VGO : BAR_QGO, 384);
            const uint32_t tag = misc[32];
            if (r == 0) mbar_wait(bar_full + QSLOT * 8, 0);
            {
                uint4 v[4];
                DSTAMP(16 + r * 16 + gw * 4, tag);
                gather4(v, pa, pa + 512, pb, pb + 512, tag, r ? 4 : 1);
                DSTAMP(18 + r * 16 + gw * 4, v[0].x ^ v[3].x);
                const float o0 = fmaf(wv[0], asf(v[0].x), wv[1] * asf(v[1].x)) + fmaf(wv[2], asf(v[2].x), wv[3] * asf(v[3].x));
                const float o1 = fmaf(wv[0], asf(v[0].y), wv[1] * asf(v[1].y)) + fmaf(wv[2], asf(v[2].y), wv[3] * asf(v[3].y));
                const float o2 = fmaf(wv[0], asf(v[0].z), wv[1] * asf(v[1].z)) + fmaf(wv[2], asf(v[2].z), wv[3] * asf(v[3].z));
                const float o3 = fmaf(wv[0], asf(v[0].w), wv[1] * asf(v[1].w)) + fmaf(wv[2], asf(v[2].w), wv[3] * asf(v[3].w));
                *reinterpret_cast<uint2*>(sgen + SM_ACT + gw * ACT_PITCH + (r ? SEG_O : SEG_Q) + lane * 8) =
                    make_uint2(pack_bf16(o0, o1), pack_bf16(o2, o3));
                bar_arrive(r ? BAR_O : BAR_Q, 384);
            }
            if (r) break;
            bar_sync(BAR_SGO, NSGO);
            {
                const uint32_t side = near_side(misc);
                const int o = AR_O + slot_off(hkv * 16 + gw * 4) + rhi * 128 + lane * 4;
                pa = prm.arena + pick(o, side);
                pb = prm.arena + pick(o + 2048, side);
            }
            if (has_ffn) {
                const int rg = cta >> 2;
                const float* ph = prm.arena + AR_Q + MAIL + ((rg >> 1) * 8 + (lane >> 4) * 4) * 512 + gw * 128 + (rg & 1) * 64 + (lane & 15) * 4;
                uint4 v[4];
                gather4(v, ph, ph + 512, ph + 1024, ph + 1536, tag, 2);
                float h0 = (asf(v[0].x) + asf(v[1].x)) + (asf(v[2].x) + asf(v[3].x));
                float h1 = (asf(v[0].y) + asf(v[1].y)) + (asf(v[2].y) + asf(v[3].y));
                float h2 = (asf(v[0].z) + asf(v[1].z)) + (asf(v[2].z) + asf(v[3].z));
                float h3 = (asf(v[0].w) + asf(v[1].w)) + (asf(v[2].w) + asf(v[3].w));
                h0 += __shfl_xor_sync(0xffffffffu, h0, 16); h1 += __shfl_xor_sync(0xffffffffu, h1, 16);
                h2 += __shfl_xor_sync(0xffffffffu, h2, 16); h3 += __shfl_xor_sync(0xffffffffu, h3, 16);
                if (lane < 16)
                    *reinterpret_cast<uint2*>(sgen + SM_ACT + gw * ACT_PITCH + SEG_H + lane * 8) =
                        make_uint2(pack_bf16(fmaxf(h0, 0.f), fmaxf(h1, 0.f)), pack_bf16(fmaxf(h2, 0.f), fmaxf(h3, 0.f)));
                bar_arrive(BAR_H, 384);
            }
            {
                const float* ps = prm.arena + AR_XS + (hkv * 16 + gw * 4 + (lane & 3)) * 8 + (rhi >> 1) * 4;
                uint4 v = ld4(ps);
                unsigned it = 0;
                while (__any_sync(0xffffffffu, badbits(v, tag) & 3u)) { v = ld4(ps); if (++it > SPIN_LIMIT) __trap(); }
                const float m = asf(((rhi & 1) ? v.z : v.x) & ~3u);
                const float l = asf((rhi & 1) ? v.w : v.y);
                float M = fmaxf(m, __shfl_xor_sync(0xffffffffu, m, 1));
                M = fmaxf(M, __shfl_xor_sync(0xffffffffu, M, 2));
                const float e = __expf(m - M);
                float L = e * l;
                L += __shfl_xor_sync(0xffffffffu, L, 1);
                L += __shfl_xor_sync(0xffffffffu, L, 2);
                const float wgt = e / L;
#pragma unroll
                for (int i = 0; i < 4; i++) wv[i] = __shfl_sync(0xffffffffu, wgt, i);
            }
        }
        PFLUSH(16 + gw * 4, 19 + gw * 4); PFLUSH(32 + gw * 4, 35 + gw * 4);
        return;
    }

    if (wix < 6 + NS) {
        const bool is_s = wix >= 6;
        float* const ar = prm.arena;
        if (wix == 6) { misc[lane] = 0xffffffffu; misc[34] = 0u; }
        if (wix == 5) {
            if (lane == 0) {
                unsigned epoch;
                asm volatile("ld.relaxed.gpu.global.u32 %0, [%1];" : "=r"(epoch) : "l"(prm.arena + AR_EPOCH) : "memory");
                misc[32] = epoch + 1;
            }
            __syncwarp();
            bar_arrive(BAR_XN, 448);
        }
        bar_sync(BAR_SGO, NSGO);
        const uint32_t side = near_side(misc);
        const int p = lane >> 2;
        const int o = slot_off(p * 4 + (cta >> 5)) + (cta & 31) * 16 + (lane & 3) * 4 + (is_s ? AR_S : AR_F);
        const float* s0 = ar + pick(o, side);
        const float* s1 = ar + pick(o + 32768, side);
        const float* s2 = ar + pick(o + 65536, side);
        const float* s3 = ar + pick(o + 98304, side);
        const bool u16 = lane & 16, u8 = lane & 8;
        uint4 v[4];
        if (!is_s) {
            const bool skip3 = p >= 4;
            if (skip3) s3 = s0;
            bar_sync(BAR_FGO, 288);
            const uint32_t tag = misc[32];
            DSTAMP(52, tag);
            gather4(v, s0, s1, s2, s3, tag, 8);
            DSTAMP(54, v[0].x ^ v[3].x);
            if (skip3) v[3] = make_uint4(0u, 0u, 0u, 0u);
            const float f = bf16r(reduce32(v, u16, u8));
            misc[lane] = __float_as_uint(bf16r(__fdividef(f, 1.f + __expf(-f))));
            PFLUSH(52, 55);
        } else {
            const int oidx = (lane >> 3) * 512 + cta * 4 + (lane & 3);
            float xfin = __bfloat162float(prm.x[oidx]);
            __nv_bfloat16* optr = prm.out + oidx;
            uint32_t tag = misc[32];
            const uint32_t zero = tag >> 8;
            uint32_t gaddr = sbase + SM_MISC + lane * 4;
            const bool bump = (cta | lane | zero) == 0;
            unsigned* const eptr = reinterpret_cast<unsigned*>(prm.arena + AR_EPOCH);
            asm volatile("" : "+l"(optr), "+f"(xfin), "+l"(s0), "+l"(s1), "+l"(s2), "+l"(s3), "+r"(tag), "+r"(gaddr));
            bar_sync(BAR_SREL, 256 + 32 * NS);
            if (wix > 6) {
                unsigned c0, c1; asm volatile("mov.u32 %0, %%clock;" : "=r"(c0));
                do { asm volatile("mov.u32 %0, %%clock;" : "=r"(c1)); } while (c1 - c0 < (unsigned)(wix - 6) * SSTAG);
            }
            unsigned it = 0;
            uint32_t gate;
            float k0, k1, t0, t1;
            uint32_t b0 = 1, b1 = 1, b2 = 1, b3 = 1;
            while (true) {
                if (b0 & 3u) v[0] = ld4(s0);
                if (b1 & 3u) v[1] = ld4(s1);
                if (b2 & 3u) v[2] = ld4(s2);
                if (b3 & 3u) v[3] = ld4(s3);
                b0 = badbits(v[0], tag); b1 = badbits(v[1], tag); b2 = badbits(v[2], tag); b3 = badbits(v[3], tag);
                const uint32_t bad = or3(b0, b1, b2) | b3;
                uint32_t done;
                asm volatile("ld.volatile.shared.u32 %0, [%1];" : "=r"(done) : "r"(sbase + SM_MISC + 34 * 4 + (DEPV & zero)) : "memory");
                asm volatile("ld.volatile.shared.u32 %0, [%1];" : "=r"(gate) : "r"(gaddr + (DEPV & zero)) : "memory");
                const float a0 = (asf(v[0].x) + asf(v[1].x)) + (asf(v[2].x) + asf(v[3].x));
                const float a1 = (asf(v[0].y) + asf(v[1].y)) + (asf(v[2].y) + asf(v[3].y));
                const float a2 = (asf(v[0].z) + asf(v[1].z)) + (asf(v[2].z) + asf(v[3].z));
                const float a3 = (asf(v[0].w) + asf(v[1].w)) + (asf(v[2].w) + asf(v[3].w));
                k0 = u16 ? a2 : a0; k1 = u16 ? a3 : a1;
                t0 = __shfl_xor_sync(0xffffffffu, u16 ? a0 : a2, 16);
                t1 = __shfl_xor_sync(0xffffffffu, u16 ? a1 : a3, 16);
                const bool again = __any_sync(0xffffffffu, (bad & 3u) || gate == 0xffffffffu);
                if (done) return;
                if (!again) break;
                if (++it > SPIN_LIMIT) __trap();
            }
            asm volatile("st.volatile.shared.u32 [%0], %1;" :: "r"(sbase + SM_MISC + 34 * 4), "r"(1u) : "memory");
            DSTAMP(50, v[0].x);
            const float e0 = k0 + t0, e1 = k1 + t1;
            float c = (u8 ? e1 : e0) + __shfl_xor_sync(0xffffffffu, u8 ? e0 : e1, 8);
            c += __shfl_xor_sync(0xffffffffu, c, 4);
            const float res = xfin + bf16r(bf16r(c) * asf(gate));
            if (!(lane & 4)) asm volatile("st.global.u16 [%0], %1;" :: "l"(optr), "h"((unsigned short)pack_bf16(res, 0.f)) : "memory");
            if (bump) *eptr = (tag == 3) ? 0u : tag;
            DSTAMP(11, __float_as_uint(res));
            PFLUSH(11, 12); PFLUSH(50, 51);
        }
        return;
    }

    const int tid = tix - (192 + 32 * NS), warp = wix - (6 + NS);
    {
        float* pr = prm.arena + pick(AR_S + slot_off(cta) + (warp >> 1) * 128, warp & 1);
        if (lane < 4) st2(pr + lane * 2, 0u, 0u);
        __syncwarp();
        if (lane == 0) {
            uint32_t v, c0, c1;
            asm volatile("mov.u32 %0, %%clock;" : "=r"(c0));
            asm volatile("atom.relaxed.gpu.global.add.u32 %0, [%1], 4;" : "=r"(v) : "l"(pr) : "memory");
            asm volatile("{\n .reg .pred p;\n setp.ne.u32 p, %1, 1;\n mov.u32 %0, 0;\n @p mov.u32 %0, %%clock;\n}" : "=r"(c1) : "r"(v));
            misc[64 + warp] = c1 - c0;
        }
        __syncwarp();
    }
    const int g = lane >> 2, t = lane & 3;
    Ring ring{bar_full, bar_empty, 0, 0u};
    const int lrow = lane & 7, lmat = lane >> 3;
    const uint32_t a_off = sbase + (warp >> 2) * 8192 + (lrow + ((lmat >> 1) << 3)) * 128 + ((((warp & 3) * 2 + (lmat & 1)) ^ lrow) << 4);
    const uint32_t b_off = sbase + SM_ACT + (lane & 3) * ACT_PITCH + lmat * 16;
    const bool hi = t >= 2;
    const int pofs = (t & 1) * 256 + warp * 16 + g + (t >> 1) * 8;
    float* const myslot = prm.arena + slot_off(cta);
    float* pub2 = myslot + (warp * 16 + g + (t >> 1) * 8) * 4 + (t & 1) * 2;
    bar_sync(BAR_XN, 448);
    const uint32_t tag = misc[32];
    MSTAMP(2, tag);

    float vs[8] = {0.f, 0.f, 0.f, 0.f, 0.f, 0.f, 0.f, 0.f};
#pragma unroll 1
    for (int sg = 0; sg < 5; sg++) {
        if (sg == 1) {
            if (tid < 2) clear4(prm.arena + AR_XS + cta * 8 + tid * 4);
            bar_sync(BAR_Q, 384);
            uint32_t qa[16];
            const uint8_t* qs = sgen + SM_ACT + (g & 3) * ACT_PITCH + SEG_Q + t * 4;
#pragma unroll
            for (int k = 0; k < 16; k++) qa[k] = *reinterpret_cast<const uint32_t*>(qs + k * 16);
            MSTAMP(4, qa[0]);
            const uint32_t k_off = sbase + (warp * 8 + lrow) * 128;
            const uint32_t sw0 = ((lmat) ^ lrow) << 4, sw1 = ((lmat + 4) ^ lrow) << 4;
            float mx = -INFINITY;
            uint8_t* sdst = sgen + SM_ACT + g * ACT_PITCH + SEG_P + (warp * 8 + 2 * t) * 2;
#pragma unroll 1
            for (int it = 0; it < KT; it++) {
                ring.wait();
                const uint32_t tb = ring.slot * TILE_B + k_off;
                uint32_t b[16];
                ldsm4(tb + sw0, b[0], b[1], b[2], b[3]);
                ldsm4(tb + sw1, b[4], b[5], b[6], b[7]);
                ldsm4(tb + 8192 + sw0, b[8], b[9], b[10], b[11]);
                ldsm4(tb + 8192 + sw1, b[12], b[13], b[14], b[15]);
                float c0[4] = {0.f, 0.f, 0.f, 0.f}, c1[4] = {0.f, 0.f, 0.f, 0.f};
#pragma unroll
                for (int k = 0; k < 8; k += 2) {
                    mma16816(c0, qa[2 * k], 0u, qa[2 * k + 1], 0u, b[2 * k], b[2 * k + 1]);
                    mma16816(c1, qa[2 * k + 2], 0u, qa[2 * k + 3], 0u, b[2 * k + 2], b[2 * k + 3]);
                }
                ring.release(lane);
                const float scale = 0.08838834764831845f;
                const uint32_t sp = pack_bf16(bf16r(c0[0] + c1[0]) * scale, bf16r(c0[1] + c1[1]) * scale);
                mx = fmaxf(mx, fmaxf(bf_lo(sp), bf_hi(sp)));
                if (lane < 16) *reinterpret_cast<uint32_t*>(sdst + it * 128) = sp;
            }
            mx = fmaxf(mx, __shfl_xor_sync(0xffffffffu, mx, 1));
            mx = fmaxf(mx, __shfl_xor_sync(0xffffffffu, mx, 2));
            if (lane < 16 && t == 0) reinterpret_cast<float*>(sgen + SM_WMAX)[warp * 4 + g] = mx;
            MSTAMP(5, __float_as_uint(mx));
            bar_sync(BAR_MMA, 256);
            const int head = warp >> 1;
            const float* wm = reinterpret_cast<const float*>(sgen + SM_WMAX) + head;
            float m = wm[0];
#pragma unroll
            for (int i = 1; i < 8; i++) m = fmaxf(m, wm[4 * i]);
            const float L2E = 1.4426950408889634f;
            uint8_t* pp = sgen + SM_ACT + head * ACT_PITCH + SEG_P + (warp & 1) * 1024 + lane * 16;
            float l = 0.f;
#pragma unroll 1
            for (int h = 0; h < 2; h++) {
                uint4 u = *reinterpret_cast<const uint4*>(pp + h * 512);
                uint32_t w[4] = {u.x, u.y, u.z, u.w};
#pragma unroll
                for (int i = 0; i < 4; i++) {
                    const float p0 = exp2f((bf_lo(w[i]) - m) * L2E), p1 = exp2f((bf_hi(w[i]) - m) * L2E);
                    l += p0 + p1;
                    w[i] = pack_bf16(p0, p1);
                }
                *reinterpret_cast<uint4*>(pp + h * 512) = make_uint4(w[0], w[1], w[2], w[3]);
            }
#pragma unroll
            for (int o = 16; o; o >>= 1) l += __shfl_xor_sync(0xffffffffu, l, o);
            if (lane == 0) reinterpret_cast<float*>(sgen + SM_LSUM)[warp] = l;
            bar_sync(BAR_MMA, 256);
            if ((warp & 1) && lane < 2) {
                const float* ls = reinterpret_cast<const float*>(sgen + SM_LSUM);
                st1(prm.arena + AR_XS + cta * 8 + head * 2 + lane, tagged(lane ? ls[warp - 1] + ls[warp] : m, tag));
            }
        }
        if ((sg == 2 || sg == 4) && !has_ffn) continue;
        const int i0 = (sg == 3) ? W1POS : (sg == 1) ? 0 : 32;
        const int i1 = (sg == 3) ? KT : (sg == 1) ? W1POS : (sg == 0) ? 34 : 33;
        const int seg = (sg == 0) ? SEG_XN + rlo * 256 : (sg == 2) ? SEG_XN + (cta & 7) * 128 : (sg == 4) ? SEG_H : SEG_P + i0 * 128;
        float* const pd = (sg == 0 ? prm.arena + AR_Q + cta * 512 : sg == 2 ? prm.arena + AR_Q + MAIL + (cta ^ 2) * 512 : myslot + AR_O) + pofs;
        uint32_t ba = b_off + seg;
        float c0[4], c1[4];
#pragma unroll
        for (int k = 0; k < 4; k++) { c0[k] = sg == 3 ? vs[k] : 0.f; c1[k] = sg == 3 ? vs[4 + k] : 0.f; }
        if (sg == 4) bar_sync(BAR_H, 384);
#pragma unroll 1
        for (int i = i0; i < i1; i++) {
            if (i == SGO) bar_arrive(BAR_SGO, NSGO);
            if (i == CLRO) { st1(pd, 0u); st1(pd + 128, 0u); st1(pd + 1024, 0u); st1(pd + 1152, 0u); }
            if (i == CLRF && has_ffn) { st2(pub2 + AR_F, 0u, 0u); st2(pub2 + AR_F + 1024, 0u, 0u); }
            if (i == CLRS) { st2(pub2 + AR_S, 0u, 0u); st2(pub2 + AR_S + 1024, 0u, 0u); }
            uint32_t a[16], b[8];
            ldsm4(ba, b[0], b[1], b[2], b[3]);
            ldsm4(ba + 64, b[4], b[5], b[6], b[7]);
            ring.wait();
            const uint32_t aa = a_off + ring.slot * TILE_B;
#pragma unroll
            for (int k = 0; k < 4; k++) ldsm4t(aa + k * 2048, a[4 * k], a[4 * k + 1], a[4 * k + 2], a[4 * k + 3]);
            mma16816(c0, a[0], a[1], a[2], a[3], b[0], b[1]);
            mma16816(c1, a[4], a[5], a[6], a[7], b[2], b[3]);
            mma16816(c0, a[8], a[9], a[10], a[11], b[4], b[5]);
            mma16816(c1, a[12], a[13], a[14], a[15], b[6], b[7]);
            ring.release(lane);
            ba += 128;
        }
        if (sg == 1) {
#pragma unroll
            for (int k = 0; k < 4; k++) { vs[k] = c0[k]; vs[4 + k] = c1[k]; }
            continue;
        }
        const uint32_t r0 = tagged(hi ? c0[2] + c1[2] : c0[0] + c1[0], tag), r1 = tagged(hi ? c0[3] + c1[3] : c0[1] + c1[1], tag);
        if (sg == 4) { st2(pub2 + AR_F, r0, r1); st2(pub2 + AR_F + 1024, r0, r1); }
        else {
            { st1(pd, r0); st1(pd + 128, r1); }
            if (sg == 3) { st1(pd + 1024, r0); st1(pd + 1152, r1); }
            if (sg != 2) bar_arrive(sg ? BAR_VGO : BAR_QGO, 384);
        }
        MSTAMP(sg == 0 ? 3 : sg == 2 ? 10 : sg + 4, r0);
    }
    bar_arrive(BAR_FGO, 288);
    {
        uint32_t a[16], b[16];
        float c[4][4];
#pragma unroll
        for (int k = 0; k < 4; k++) { c[k][0] = 0.f; c[k][1] = 0.f; c[k][2] = 0.f; c[k][3] = 0.f; }
        pub2 += AR_S;
        constexpr int KPP = 4 / NPC;
        const uint32_t ap_off = a_off - (warp >> 2) * (8192 - 8192 / NPC);
#pragma unroll
        for (int i = 0; i < 2; i++) {
            if (i >= 2 - NSPT) {
                if (i == 0) {
                    bar_sync(BAR_O, 384);
#pragma unroll
                    for (int k = 0; k < 4; k++) ldsm4(b_off + SEG_O + k * 64, b[4 * k], b[4 * k + 1], b[4 * k + 2], b[4 * k + 3]);
                    MSTAMP(12, b[15]);
                }
                const uint32_t aa = ap_off + ring.slot * TILE_B;
#pragma unroll
                for (int q = 0; q < NPC; q++) {
                    if (q == 0) mbar_spin(ring.full + ring.slot * 8, ring.phase);
                    else mbar_spin(ring.full + (2 * NSLOT + (i - (2 - NSPT)) * (NPC - 1) + q - 1) * 8, 0);
#pragma unroll
                    for (int kk = 0; kk < KPP; kk++) {
                        const int k = q * KPP + kk;
                        ldsm4t(aa + q * (TILE_B / NPC) + kk * 2048, a[4 * k], a[4 * k + 1], a[4 * k + 2], a[4 * k + 3]);
                    }
#pragma unroll
                    for (int kk = 0; kk < KPP; kk++) {
                        const int k = q * KPP + kk;
                        mma16816(c[k], a[4 * k], a[4 * k + 1], a[4 * k + 2], a[4 * k + 3], b[8 * i + 2 * k], b[8 * i + 2 * k + 1]);
                    }
                }
                ring.next();
            } else {
                ring.wait();
                const uint32_t aa = a_off + ring.slot * TILE_B;
#pragma unroll
                for (int k = 0; k < 4; k++) ldsm4t(aa + k * 2048, a[4 * k], a[4 * k + 1], a[4 * k + 2], a[4 * k + 3]);
                ring.next();
                bar_sync(BAR_O, 384);
#pragma unroll
                for (int k = 0; k < 4; k++) ldsm4(b_off + SEG_O + k * 64, b[4 * k], b[4 * k + 1], b[4 * k + 2], b[4 * k + 3]);
                MSTAMP(12, b[15]);
#pragma unroll
                for (int k = 0; k < 4; k++) mma16816(c[k], a[4 * k], a[4 * k + 1], a[4 * k + 2], a[4 * k + 3], b[2 * k], b[2 * k + 1]);
            }
        }
        MSTAMP(15, a[15]);
        const float r0 = ((hi ? c[0][2] : c[0][0]) + (hi ? c[1][2] : c[1][0])) + ((hi ? c[2][2] : c[2][0]) + (hi ? c[3][2] : c[3][0]));
        const float r1 = ((hi ? c[0][3] : c[0][1]) + (hi ? c[1][3] : c[1][1])) + ((hi ? c[2][3] : c[2][1]) + (hi ? c[3][3] : c[3][1]));
        const uint32_t u0 = tagged(r0, tag), u1 = tagged(r1, tag);
        st2(pub2, u0, u1);
        st2(pub2 + 1024, u0, u1);
        bar_arrive(BAR_SREL, 256 + 32 * NS);
        MSTAMP(9, u0);
    }
}

typedef CUresult (*EncodeFn)(CUtensorMap*, CUtensorMapDataType, cuuint32_t, void*, const cuuint64_t*, const cuuint64_t*,
                             const cuuint32_t*, const cuuint32_t*, CUtensorMapInterleave, CUtensorMapSwizzle,
                             CUtensorMapL2promotion, CUtensorMapFloatOOBfill);

void make_map(EncodeFn enc, CUtensorMap* m, const void* base, uint64_t rows, uint64_t cols, uint32_t box_rows = 64) {
    cuuint64_t dims[3] = {64, rows, cols / 64};
    cuuint64_t strides[2] = {cols * 2, 128};
    cuuint32_t box[3] = {64, box_rows, 2};
    cuuint32_t es[3] = {1, 1, 1};
    enc(m, CU_TENSOR_MAP_DATA_TYPE_BFLOAT16, 3, const_cast<void*>(base), dims, strides, box, es,
        CU_TENSOR_MAP_INTERLEAVE_NONE, CU_TENSOR_MAP_SWIZZLE_128B, PROMO,
        CU_TENSOR_MAP_FLOAT_OOB_FILL_NONE);
}

}

extern "C" void kernel_launch(void* const* d_in, const int* in_sizes, int n_in, void* d_out, int out_size) {
    (void)in_sizes; (void)n_in; (void)out_size;
    static EncodeFn enc = nullptr;
    static void* arena_ptr = nullptr;
    if (!enc) {
        void* fn = nullptr;
        cudaDriverEntryPointQueryResult qr;
        cudaGetDriverEntryPoint("cuTensorMapEncodeTiled", &fn, cudaEnableDefault, &qr);
        enc = (EncodeFn)fn;
        cudaGetSymbolAddress(&arena_ptr, g_arena);
        cudaFuncSetAttribute(fused_decode_kernel, cudaFuncAttributeMaxDynamicSharedMemorySize, SM_TOTAL + 1024);
    }
    Params prm;
    make_map(enc, &prm.m[0], d_in[3], 512, 4096);
    make_map(enc, &prm.m[1], d_in[6], 512, 1792);
    make_map(enc, &prm.m[2], d_in[1], 4ull * 8 * 16384, 128);
    make_map(enc, &prm.m[3], d_in[2], 4ull * 8 * 16384, 128);
    make_map(enc, &prm.m[4], d_in[7], 1792, 512);
    make_map(enc, &prm.m[5], d_in[4], 4096, 512);
    make_map(enc, &prm.m[6], d_in[4], 4096, 512, 64 / NPC);
    prm.raw[0] = (const char*)d_in[2];
    prm.raw[1] = (const char*)d_in[7];
    prm.raw[2] = (const char*)d_in[4];
    prm.x = (const __nv_bfloat16*)d_in[0];
    prm.out = (__nv_bfloat16*)d_out;
#define WIN 0
    prm.arena = (float*)((((uintptr_t)arena_ptr + 0x1fffffull) & ~0x1fffffull) + (uintptr_t)(WIN) * 0x200000ull);
#define LTHREADS NTHREADS
    fused_decode_kernel<<<NCTA, LTHREADS, SM_TOTAL + 1024>>>(prm);
}
```

```cpp
#include <cuda_runtime.h>
#include <cuda_bf16.h>
#include <cuda.h>
#include <stdint.h>

namespace {

constexpr int NCTA     = 128;
constexpr int NFFN     = 112;
constexpr int NSLOT    = 13;
constexpr int TILE_B   = 16384;
constexpr int KT       = 16;
constexpr int NS       = 3;
constexpr int NTHREADS = 448 + 32 * NS;

constexpr int TAU      = 657;
constexpr int LEAD     = 22;
constexpr int INFLIGHT = 8;
constexpr int TAILCAP  = 3;
constexpr int W1POS    = 6;
constexpr int QSLOT = 5;
constexpr int SGO   = 10;
constexpr int CLRO = 12, CLRF = 13, CLRS = 14;
constexpr unsigned SSTAG = 150;

constexpr int SEG_XN = 0;
constexpr int SEG_P  = 1024;
constexpr int SEG_H  = 3072;
constexpr int SEG_O  = 3200;
constexpr int SEG_Q  = 3456;
constexpr int ACT_PITCH = 3712 + 16;
constexpr int SM_ACT   = NSLOT * TILE_B;
constexpr int SM_WMAX  = SM_ACT + 4 * ACT_PITCH;
constexpr int SM_LSUM  = SM_WMAX + 128;
constexpr int SM_MISC  = SM_LSUM + 32;
constexpr int SM_BAR   = SM_MISC + 256;
constexpr int SM_TOTAL = SM_BAR + (2 * NSLOT + 2) * 8;
static_assert(SM_TOTAL + 1024 <= 232448, "smem");

constexpr int BAR_MMA = 1, BAR_XN = 2, BAR_Q = 3, BAR_H = 4, BAR_O = 5, BAR_VGO = 6, BAR_QGO = 7, BAR_SGO = 8,
              BAR_FGO = 9, BAR_SREL = 10;
constexpr int N_SGO = 416 + 32 * NS, N_SREL = 256 + 32 * NS;

__device__ __align__(4096) float g_arena[1 << 20];
constexpr int AR_O = 0, AR_F = 131072, AR_S = 262144, AR_Q = 393216, AR_H = 458752;
constexpr int AR_XS = AR_F + (NFFN / 2) * 2048;
constexpr int AR_EPOCH = AR_XS + 2048;
constexpr uint32_t HOME_MASK = (1u << 12) | (1u << 13) | (1u << 16) | (1u << 17) | (1u << 19);

struct Params {
    CUtensorMap m[6];
    const char* raw[3];
    const __nv_bfloat16* x;
    __nv_bfloat16* out;
    float* arena;
};

constexpr unsigned SPIN_LIMIT = 1u << 20;

__device__ __forceinline__ int slot_off(int producer) { return (producer >> 1) * 2048 + (producer & 1) * 512; }
__device__ __forceinline__ uint32_t parity(int off) { return __popc(((uint32_t)off << 2) & HOME_MASK) & 1u; }
__device__ __forceinline__ int pick(int off, uint32_t side) { return off + (int)((parity(off) ^ side) << 10); }

__device__ __forceinline__ void mbar_init(uint32_t bar, uint32_t cnt) {
    asm volatile("mbarrier.init.shared::cta.b64 [%0], %1;" :: "r"(bar), "r"(cnt) : "memory");
}
__device__ __forceinline__ void mbar_expect_tx(uint32_t bar, uint32_t bytes) {
    asm volatile("mbarrier.arrive.expect_tx.shared::cta.b64 _, [%0], %1;" :: "r"(bar), "r"(bytes) : "memory");
}
__device__ __forceinline__ void mbar_arrive(uint32_t bar) {
    asm volatile("mbarrier.arrive.shared::cta.b64 _, [%0];" :: "r"(bar) : "memory");
}
__device__ __forceinline__ bool mbar_test(uint32_t bar, uint32_t par) {
    uint32_t ok;
    asm volatile("{\n .reg .pred p;\n mbarrier.test_wait.parity.shared::cta.b64 p, [%1], %2;\n selp.u32 %0, 1, 0, p;\n}"
                 : "=r"(ok) : "r"(bar), "r"(par) : "memory");
    return ok;
}
__device__ __forceinline__ void mbar_wait(uint32_t bar, uint32_t par) {
    uint32_t ok, it = 0;
    while (true) {
        asm volatile("{\n .reg .pred p;\n mbarrier.try_wait.parity.shared::cta.b64 p, [%1], %2, %3;\n selp.u32 %0, 1, 0, p;\n}"
                     : "=r"(ok) : "r"(bar), "r"(par), "r"(10000) : "memory");
        if (ok) break;
        if (++it > SPIN_LIMIT) __trap();
    }
}
__device__ __forceinline__ void mbar_spin(uint32_t bar, uint32_t par) {
    uint32_t ok, it = 0;
    while (true) {
        asm volatile("{\n .reg .pred p;\n mbarrier.try_wait.parity.shared::cta.b64 p, [%1], %2;\n selp.u32 %0, 1, 0, p;\n}"
                     : "=r"(ok) : "r"(bar), "r"(par) : "memory");
        if (ok) break;
        if (++it > 16 * SPIN_LIMIT) __trap();
    }
}
__device__ __forceinline__ void tma_tile(uint32_t dst, const CUtensorMap* tm, int row, int half, uint32_t bar) {
    asm volatile("cp.async.bulk.tensor.3d.shared::cluster.global.mbarrier::complete_tx::bytes.L2::cache_hint [%0], [%1, {%3, %4, %5}], [%2], %6;"
                 :: "r"(dst), "l"(tm), "r"(bar), "r"(0), "r"(row), "r"(half), "l"(0x12F0000000000000ull) : "memory");
}
__device__ __forceinline__ void ldsm4(uint32_t addr, uint32_t* r) {
    asm volatile("ldmatrix.sync.aligned.m8n8.x4.shared.b16 {%0,%1,%2,%3}, [%4];"
                 : "=r"(r[0]), "=r"(r[1]), "=r"(r[2]), "=r"(r[3]) : "r"(addr) : "memory");
}
__device__ __forceinline__ void ldsm4t(uint32_t addr, uint32_t* r) {
    asm volatile("ldmatrix.sync.aligned.m8n8.x4.trans.shared.b16 {%0,%1,%2,%3}, [%4];"
                 : "=r"(r[0]), "=r"(r[1]), "=r"(r[2]), "=r"(r[3]) : "r"(addr) : "memory");
}
__device__ __forceinline__ void mma16816(float (&c)[4], uint32_t a0, uint32_t a1, uint32_t a2, uint32_t a3,
                                         uint32_t b0, uint32_t b1) {
    asm volatile("mma.sync.aligned.m16n8k16.row.col.f32.bf16.bf16.f32 {%0,%1,%2,%3}, {%4,%5,%6,%7}, {%8,%9}, {%0,%1,%2,%3};"
                 : "+f"(c[0]), "+f"(c[1]), "+f"(c[2]), "+f"(c[3])
                 : "r"(a0), "r"(a1), "r"(a2), "r"(a3), "r"(b0), "r"(b1));
}
__device__ __forceinline__ void bar_sync(int id, int n) { asm volatile("bar.sync %0, %1;" :: "r"(id), "r"(n) : "memory"); }
__device__ __forceinline__ void bar_arrive(int id, int n) { asm volatile("bar.arrive %0, %1;" :: "r"(id), "r"(n) : "memory"); }
__device__ __forceinline__ unsigned gtime32() { unsigned t; asm volatile("mov.u32 %0, %%globaltimer_lo;" : "=r"(t)); return t; }
__device__ __forceinline__ unsigned clock32() { unsigned t; asm volatile("mov.u32 %0, %%clock;" : "=r"(t)); return t; }
__device__ __forceinline__ void delay(unsigned clocks) { const unsigned c0 = clock32(); while (clock32() - c0 < clocks) {} }

__device__ __forceinline__ float bf16r(float v) {
    uint32_t d; asm("cvt.rn.bf16x2.f32 %0, %1, %2;" : "=r"(d) : "f"(v), "f"(0.f));
    return __uint_as_float(d);
}
__device__ __forceinline__ uint32_t pack_bf16(float lo, float hi) {
    uint32_t d; asm("cvt.rn.bf16x2.f32 %0, %1, %2;" : "=r"(d) : "f"(hi), "f"(lo));
    return d;
}
__device__ __forceinline__ float bf_lo(uint32_t u) { return __uint_as_float(u << 16); }
__device__ __forceinline__ float bf_hi(uint32_t u) { return __uint_as_float(u & 0xffff0000u); }
__device__ __forceinline__ float asf(uint32_t u) { return __uint_as_float(u); }

__device__ __forceinline__ uint32_t tagged(float v, uint32_t tag) { return (__float_as_uint(v) & ~3u) | tag; }
__device__ __forceinline__ void st1(float* p, uint32_t u) {
    asm volatile("st.relaxed.gpu.global.u32 [%0], %1;" :: "l"(p), "r"(u) : "memory");
}
__device__ __forceinline__ void st2(float* p, uint32_t u0, uint32_t u1) {
    asm volatile("st.relaxed.gpu.global.v2.u32 [%0], {%1, %2};" :: "l"(p), "r"(u0), "r"(u1) : "memory");
}
__device__ __forceinline__ uint4 ld4(const float* p) {
    uint4 v;
    asm volatile("ld.relaxed.gpu.global.v4.u32 {%0,%1,%2,%3}, [%4];" : "=r"(v.x), "=r"(v.y), "=r"(v.z), "=r"(v.w) : "l"(p) : "memory");
    return v;
}
__device__ __forceinline__ uint32_t badbits(const uint4& v, uint32_t tag) {
    uint32_t a, b;
    asm("lop3.b32 %0, %1, %2, %3, 0x7e;" : "=r"(a) : "r"(v.x), "r"(tag), "r"(v.y));
    asm("lop3.b32 %0, %1, %2, %3, 0x7e;" : "=r"(b) : "r"(v.z), "r"(tag), "r"(v.w));
    return a | b;
}
__device__ __forceinline__ void gather4(uint4 (&v)[4], const float* p0, const float* p1, const float* p2, const float* p3, uint32_t tag) {
    v[0] = ld4(p0); v[1] = ld4(p1); v[2] = ld4(p2); v[3] = ld4(p3);
    unsigned it = 0;
    while (true) {
        const uint32_t b0 = badbits(v[0], tag), b1 = badbits(v[1], tag), b2 = badbits(v[2], tag), b3 = badbits(v[3], tag);
        if (!__any_sync(0xffffffffu, ((b0 | b1) | (b2 | b3)) & 3u)) break;
        if (b0 & 3u) v[0] = ld4(p0);
        if (b1 & 3u) v[1] = ld4(p1);
        if (b2 & 3u) v[2] = ld4(p2);
        if (b3 & 3u) v[3] = ld4(p3);
        if (++it > SPIN_LIMIT) __trap();
    }
}
__device__ __forceinline__ float4 sum4(const uint4 (&v)[4]) {
    return make_float4((asf(v[0].x) + asf(v[1].x)) + (asf(v[2].x) + asf(v[3].x)), (asf(v[0].y) + asf(v[1].y)) + (asf(v[2].y) + asf(v[3].y)),
                       (asf(v[0].z) + asf(v[1].z)) + (asf(v[2].z) + asf(v[3].z)), (asf(v[0].w) + asf(v[1].w)) + (asf(v[2].w) + asf(v[3].w)));
}
__device__ __forceinline__ uint32_t near_side(volatile uint32_t* misc) {
    const uint32_t m0 = min(min(misc[40], misc[42]), min(misc[44], misc[46]));
    const uint32_t m1 = min(min(misc[41], misc[43]), min(misc[45], misc[47]));
    return m1 < m0;
}

struct Ring {
    uint32_t full, empty;
    int slot; uint32_t phase;
    __device__ __forceinline__ void wait() { mbar_wait(full + slot * 8, phase); }
    __device__ __forceinline__ void next() { if (++slot == NSLOT) { slot = 0; phase ^= 1; } }
    __device__ __forceinline__ void release(int lane) {
        __syncwarp();
        if (lane == 0) mbar_arrive(empty + slot * 8);
        next();
    }
};

__global__ void __launch_bounds__(NTHREADS, 1)
fused_decode_kernel(const __grid_constant__ Params prm) {
    extern __shared__ uint8_t smem_raw[];
    const uint32_t sbase = ((uint32_t)__cvta_generic_to_shared(smem_raw) + 1023u) & ~1023u;
    uint8_t* sgen = smem_raw + (sbase - (uint32_t)__cvta_generic_to_shared(smem_raw));
    const int cta = blockIdx.x;
    const int hkv = cta >> 4, rhi = (cta >> 2) & 3, rlo = cta & 3;
    const bool has_ffn = cta < NFFN;
    const uint32_t bar_full = sbase + SM_BAR, bar_empty = bar_full + NSLOT * 8, bar_half = bar_empty + NSLOT * 8;

    if (threadIdx.x - 1u < 31u) return;
    if (threadIdx.x == 0) {
        const unsigned t0 = gtime32();
        mbar_init(bar_full, 1);
        asm volatile("fence.mbarrier_init.release.cluster;" ::: "memory");
        mbar_expect_tx(bar_full, TILE_B);
        tma_tile(sbase, &prm.m[0], rlo * 128, (cta >> 2) * 2, bar_full);
#pragma unroll
        for (int i = 1; i < 2 * NSLOT + 2; i++) mbar_init(bar_full + i * 8, (i < NSLOT || i >= 2 * NSLOT) ? 1 : 8);
        asm volatile("fence.mbarrier_init.release.cluster;" ::: "memory");
        asm volatile("barrier.arrive %0, %1;" :: "n"(BAR_XN), "n"(448) : "memory");
        const int kvrow = (rhi * 8 + hkv) * 16384 + 12288 + rlo * 64;
        const int toff = ((((cta >> 2) * 13) & 31) * TAU) / 32 - (LEAD * TAU) / 16;
        constexpr int P_W1 = 18 + W1POS, P_W2 = 35, P_END = 38;
        int slot = 1; uint32_t eph = 1;
        int fslot = 0; uint32_t fph = 0;
        int landed = 0, issued = 1;
#pragma unroll 1
        for (int v = 1; v < P_END; v++) {
            int mi, row, half;
            if (v == 1)          { mi = 0; row = rlo * 128 + 64; half = (cta >> 2) * 2; }
            else if (v == P_W1)  { mi = 1; row = (cta & 7) * 64; half = (cta >> 3) * 2; }
            else if (v < P_W2)   { const int j = v - 2 - (v > P_W1); mi = 2 + (j >> 4); row = kvrow + (j & 15) * 256; half = 0; }
            else if (v == P_W2)  { mi = 4; row = (cta >> 2) * 64; half = rlo * 2; }
            else                 { mi = 5; row = (cta >> 2) * 128 + (v - P_W2 - 1) * 64; half = rlo * 2; }
            if (v < 6) asm volatile("prefetch.tensormap [%0];" :: "l"(&prm.m[v]) : "memory");
            if (v == 10) asm volatile("cp.async.bulk.prefetch.L2.global [%0], 128;" :: "l"(prm.raw[0] + (size_t)kvrow * 256) : "memory");
            if (v == 27) {
                if (has_ffn) asm volatile("cp.async.bulk.prefetch.L2.global [%0], 128;" :: "l"(prm.raw[1] + (cta >> 2) * 65536 + rlo * 256) : "memory");
                asm volatile("cp.async.bulk.prefetch.L2.global [%0], 128;" :: "l"(prm.raw[2] + (cta >> 2) * 131072 + rlo * 256) : "memory");
            }
            if (!has_ffn && (v == P_W1 || v == P_W2)) continue;
            const int need = issued + 1 - (v >= P_W2 ? TAILCAP : INFLIGHT);
            while (landed < need) {
                mbar_wait(bar_full + fslot * 8, fph);
                if (++fslot == NSLOT) { fslot = 0; fph ^= 1; }
                landed++;
            }
            if (issued >= NSLOT) mbar_wait(bar_empty + slot * 8, eph);
            {
                const int due = (v - (!has_ffn && v > P_W2)) * TAU + toff;
                int s2 = slot - 2; uint32_t par = eph ^ 1;
                if (s2 < 0) { s2 += NSLOT; par ^= 1; }
                while ((int)(gtime32() - t0) < due) {
                    if (v > 4 && mbar_test(bar_full + s2 * 8, par)) break;
                }
            }
            const uint32_t dst = sbase + slot * TILE_B, bf = bar_full + slot * 8;
            if (v > P_W2) {
                const uint32_t bh = bar_half + (v - P_W2 - 1) * 8;
                mbar_expect_tx(bf, TILE_B / 2);
                tma_tile(dst, &prm.m[5], row, half, bf);
                mbar_expect_tx(bh, TILE_B / 2);
                tma_tile(dst + TILE_B / 2, &prm.m[5], row + 32, half, bh);
            } else {
                mbar_expect_tx(bf, TILE_B);
                tma_tile(dst, &prm.m[mi], row, half, bf);
            }
            if (++slot == NSLOT) { slot = 0; eph ^= 1; }
            issued++;
        }
    }
    int tix;
    asm volatile("mov.u32 %0, %%tid.x;" : "=r"(tix));
    if (tix == 0) return;
    const int lane = tix & 31;
    const int wix = __shfl_sync(0xffffffffu, tix >> 5, 0);
    volatile uint32_t* misc = reinterpret_cast<volatile uint32_t*>(sgen + SM_MISC);

    if (wix < 5) {
        const int gw = wix - 1;
        {
            const uint4* xr = reinterpret_cast<const uint4*>(prm.x + gw * 512);
            const uint4 u0 = __ldg(xr + lane), u1 = __ldg(xr + 32 + lane);
            const uint32_t w[8] = {u0.x, u0.y, u0.z, u0.w, u1.x, u1.y, u1.z, u1.w};
            float s = 0.f;
#pragma unroll
            for (int i = 0; i < 8; i++) s += bf_lo(w[i]) + bf_hi(w[i]);
#pragma unroll
            for (int o = 16; o; o >>= 1) s += __shfl_xor_sync(0xffffffffu, s, o);
            const float mean = s * (1.f / 512.f);
            float vs = 0.f;
#pragma unroll
            for (int i = 0; i < 8; i++) { const float d0 = bf_lo(w[i]) - mean, d1 = bf_hi(w[i]) - mean; vs += d0 * d0 + d1 * d1; }
#pragma unroll
            for (int o = 16; o; o >>= 1) vs += __shfl_xor_sync(0xffffffffu, vs, o);
            const float mb = bf16r(mean);
            const float den = bf16r(sqrtf(bf16r(bf16r(vs * (1.f / 512.f)) + 1e-5f)));
#pragma unroll 1
            for (int h = 0; h < 2; h++) {
                const uint4 u = h ? u1 : u0;
                const uint32_t uu[4] = {u.x, u.y, u.z, u.w};
                uint32_t r[4];
#pragma unroll
                for (int i = 0; i < 4; i++)
                    r[i] = pack_bf16(__fdiv_rn(bf16r(bf_lo(uu[i]) - mb), den), __fdiv_rn(bf16r(bf_hi(uu[i]) - mb), den));
                *reinterpret_cast<uint4*>(sgen + SM_ACT + gw * ACT_PITCH + SEG_XN + h * 512 + lane * 16) = make_uint4(r[0], r[1], r[2], r[3]);
            }
        }
        bar_arrive(BAR_XN, 448);
        float wv[4] = {1.f, 1.f, 1.f, 1.f};
        const float* pa = prm.arena + AR_Q + (hkv * 16 + gw * 4) * 512 + rhi * 128 + lane * 4;
        const float* pb = pa + 1024;
#pragma unroll 1
        for (int r = 0; r < 2; r++) {
            bar_sync(r ? BAR_VGO : BAR_QGO, 384);
            const uint32_t tag = misc[32];
            if (r == 0) mbar_wait(bar_full + QSLOT * 8, 0);
            {
                uint4 v[4];
                gather4(v, pa, pa + 512, pb, pb + 512, tag);
                const float o0 = fmaf(wv[0], asf(v[0].x), wv[1] * asf(v[1].x)) + fmaf(wv[2], asf(v[2].x), wv[3] * asf(v[3].x));
                const float o1 = fmaf(wv[0], asf(v[0].y), wv[1] * asf(v[1].y)) + fmaf(wv[2], asf(v[2].y), wv[3] * asf(v[3].y));
                const float o2 = fmaf(wv[0], asf(v[0].z), wv[1] * asf(v[1].z)) + fmaf(wv[2], asf(v[2].z), wv[3] * asf(v[3].z));
                const float o3 = fmaf(wv[0], asf(v[0].w), wv[1] * asf(v[1].w)) + fmaf(wv[2], asf(v[2].w), wv[3] * asf(v[3].w));
                *reinterpret_cast<uint2*>(sgen + SM_ACT + gw * ACT_PITCH + (r ? SEG_O : SEG_Q) + lane * 8) =
                    make_uint2(pack_bf16(o0, o1), pack_bf16(o2, o3));
                bar_arrive(r ? BAR_O : BAR_Q, 384);
            }
            if (r) break;
            bar_sync(BAR_SGO, N_SGO);
            {
                const uint32_t side = near_side(misc);
                const int o = AR_O + slot_off(hkv * 16 + gw * 4) + rhi * 128 + lane * 4;
                pa = prm.arena + pick(o, side);
                pb = prm.arena + pick(o + 2048, side);
            }
            if (has_ffn) {
                const int rg = cta >> 2;
                const float* ph = prm.arena + AR_H + ((rg >> 1) * 8 + (lane >> 4) * 4) * 512 + gw * 128 + (rg & 1) * 64 + (lane & 15) * 4;
                uint4 v[4];
                gather4(v, ph, ph + 512, ph + 1024, ph + 1536, tag);
                float4 h = sum4(v);
                h.x += __shfl_xor_sync(0xffffffffu, h.x, 16); h.y += __shfl_xor_sync(0xffffffffu, h.y, 16);
                h.z += __shfl_xor_sync(0xffffffffu, h.z, 16); h.w += __shfl_xor_sync(0xffffffffu, h.w, 16);
                if (lane < 16)
                    *reinterpret_cast<uint2*>(sgen + SM_ACT + gw * ACT_PITCH + SEG_H + lane * 8) =
                        make_uint2(pack_bf16(fmaxf(h.x, 0.f), fmaxf(h.y, 0.f)), pack_bf16(fmaxf(h.z, 0.f), fmaxf(h.w, 0.f)));
                bar_arrive(BAR_H, 384);
            }
            {
                const float* ps = prm.arena + AR_XS + (hkv * 16 + gw * 4 + (lane & 3)) * 8 + (rhi >> 1) * 4;
                uint4 v = ld4(ps);
                unsigned it = 0;
                while (__any_sync(0xffffffffu, badbits(v, tag) & 3u)) { v = ld4(ps); if (++it > SPIN_LIMIT) __trap(); }
                const float m = asf(((rhi & 1) ? v.z : v.x) & ~3u);
                const float l = asf((rhi & 1) ? v.w : v.y);
                float M = fmaxf(m, __shfl_xor_sync(0xffffffffu, m, 1));
                M = fmaxf(M, __shfl_xor_sync(0xffffffffu, M, 2));
                const float e = __expf(m - M);
                float L = e * l;
                L += __shfl_xor_sync(0xffffffffu, L, 1);
                L += __shfl_xor_sync(0xffffffffu, L, 2);
                const float wgt = e / L;
#pragma unroll
                for (int i = 0; i < 4; i++) wv[i] = __shfl_sync(0xffffffffu, wgt, i);
            }
        }
        return;
    }

    if (wix < 6 + NS) {
        const bool is_s = wix >= 6;
        if (wix == 6) { misc[lane] = 0xffffffffu; misc[33] = 0u; }
        if (wix == 5) {
            if (lane == 0) {
                unsigned epoch;
                asm volatile("ld.relaxed.gpu.global.u32 %0, [%1];" : "=r"(epoch) : "l"(prm.arena + AR_EPOCH) : "memory");
                misc[32] = epoch + 1;
            }
            __syncwarp();
            bar_arrive(BAR_XN, 448);
        }
        bar_sync(BAR_SGO, N_SGO);
        const uint32_t side = near_side(misc);
        const uint32_t tag = misc[32];
        const int p = lane >> 2;
        const int o = slot_off(p * 4 + (cta >> 5)) + (cta & 31) * 16 + (lane & 3) * 4 + (is_s ? AR_S : AR_F);
        const float* s0 = prm.arena + pick(o, side);
        const float* s1 = prm.arena + pick(o + 32768, side);
        const float* s2 = prm.arena + pick(o + 65536, side);
        const float* s3 = prm.arena + pick(o + 98304, side);
        const bool u16 = lane & 16, u8 = lane & 8;
        uint4 v[4];
        if (!is_s) {
            const bool skip3 = p >= 4;
            if (skip3) s3 = s0;
            bar_sync(BAR_FGO, 288);
            gather4(v, s0, s1, s2, s3, tag);
            if (skip3) v[3] = make_uint4(0u, 0u, 0u, 0u);
            const float4 a = sum4(v);
            const float e0 = (u16 ? a.z : a.x) + __shfl_xor_sync(0xffffffffu, u16 ? a.x : a.z, 16);
            const float e1 = (u16 ? a.w : a.y) + __shfl_xor_sync(0xffffffffu, u16 ? a.y : a.w, 16);
            float c = (u8 ? e1 : e0) + __shfl_xor_sync(0xffffffffu, u8 ? e0 : e1, 8);
            c += __shfl_xor_sync(0xffffffffu, c, 4);
            const float f = bf16r(c);
            misc[lane] = __float_as_uint(bf16r(__fdividef(f, 1.f + __expf(-f))));
        } else {
            const int oidx = (lane >> 3) * 512 + cta * 4 + (lane & 3);
            const float xfin = __bfloat162float(prm.x[oidx]);
            __nv_bfloat16* const optr = prm.out + oidx;
            const uint32_t zero = tag >> 8;
            const uint32_t gaddr = sbase + SM_MISC + lane * 4;
            const bool bump = (cta | lane | zero) == 0;
            bar_sync(BAR_SREL, N_SREL);
            if (wix > 6) delay((wix - 6) * SSTAG);
            unsigned it = 0;
            uint32_t gate, b0 = 1, b1 = 1, b2 = 1, b3 = 1;
            float k0, k1, t0, t1;
            while (true) {
                if (b0 & 3u) v[0] = ld4(s0);
                if (b1 & 3u) v[1] = ld4(s1);
                if (b2 & 3u) v[2] = ld4(s2);
                if (b3 & 3u) v[3] = ld4(s3);
                b0 = badbits(v[0], tag); b1 = badbits(v[1], tag); b2 = badbits(v[2], tag); b3 = badbits(v[3], tag);
                const uint32_t bad = (b0 | b1) | (b2 | b3);
                uint32_t done;
                asm volatile("ld.volatile.shared.u32 %0, [%1];" : "=r"(done) : "r"(sbase + SM_MISC + 33 * 4 + (bad & zero)) : "memory");
                asm volatile("ld.volatile.shared.u32 %0, [%1];" : "=r"(gate) : "r"(gaddr + (bad & zero)) : "memory");
                const float4 a = sum4(v);
                k0 = u16 ? a.z : a.x; k1 = u16 ? a.w : a.y;
                t0 = __shfl_xor_sync(0xffffffffu, u16 ? a.x : a.z, 16);
                t1 = __shfl_xor_sync(0xffffffffu, u16 ? a.y : a.w, 16);
                const bool again = __any_sync(0xffffffffu, (bad & 3u) || gate == 0xffffffffu);
                if (done) return;
                if (!again) break;
                if (++it > 16 * SPIN_LIMIT) __trap();
            }
            misc[33] = 1u;
            const float e0 = k0 + t0, e1 = k1 + t1;
            float c = (u8 ? e1 : e0) + __shfl_xor_sync(0xffffffffu, u8 ? e0 : e1, 8);
            c += __shfl_xor_sync(0xffffffffu, c, 4);
            const float res = xfin + bf16r(bf16r(c) * asf(gate));
            if (!(lane & 4)) *optr = __float2bfloat16_rn(res);
            if (bump) *reinterpret_cast<unsigned*>(prm.arena + AR_EPOCH) = (tag == 3) ? 0u : tag;
        }
        return;
    }

    const int warp = wix - (6 + NS);
    {
        const int oq = AR_Q + cta * 512 + (warp >> 1) * 128, oh = AR_H + (cta ^ 2) * 512 + (warp >> 1) * 128;
        float* pr = prm.arena + (((parity(oq) ^ warp) & 1) ? oh : oq);
        if (lane < 4) st2(pr + lane * 2, 0u, 0u);
        bar_sync(BAR_MMA, 256);
        delay(300);
        if (lane == 0) {
            uint32_t v, c1;
            const uint32_t c0 = clock32();
            asm volatile("atom.relaxed.gpu.global.add.u32 %0, [%1], 4;" : "=r"(v) : "l"(pr) : "memory");
            asm volatile("{\n .reg .pred p;\n setp.ne.u32 p, %1, 1;\n mov.u32 %0, 0;\n @p mov.u32 %0, %%clock;\n}" : "=r"(c1) : "r"(v));
            misc[40 + warp] = c1 - c0;
        }
        __syncwarp();
    }
    const int g = lane >> 2, t = lane & 3;
    Ring ring{bar_full, bar_empty, 0, 0u};
    const int lrow = lane & 7, lmat = lane >> 3;
    const uint32_t a_lane = (lrow + ((lmat >> 1) << 3)) * 128 + ((((warp & 3) * 2 + (lmat & 1)) ^ lrow) << 4);
    const uint32_t a_off = sbase + (warp >> 2) * 8192 + a_lane;
    const uint32_t b_off = sbase + SM_ACT + (lane & 3) * ACT_PITCH + lmat * 16;
    const bool hi = t >= 2;
    const int pofs = (t & 1) * 256 + warp * 16 + g + (t >> 1) * 8;
    float* const myslot = prm.arena + slot_off(cta);
    float* const pub2 = myslot + (warp * 16 + g + (t >> 1) * 8) * 4 + (t & 1) * 2;
    bar_sync(BAR_XN, 448);
    const uint32_t tag = misc[32];

    float vs[8] = {0.f, 0.f, 0.f, 0.f, 0.f, 0.f, 0.f, 0.f};
#pragma unroll 1
    for (int sg = 0; sg < 5; sg++) {
        if (sg == 1) {
            if (warp == 0 && lane < 4) st2(prm.arena + AR_XS + cta * 8 + lane * 2, 0u, 0u);
            bar_sync(BAR_Q, 384);
            uint32_t qa[16];
            const uint8_t* qs = sgen + SM_ACT + (g & 3) * ACT_PITCH + SEG_Q + t * 4;
#pragma unroll
            for (int k = 0; k < 16; k++) qa[k] = *reinterpret_cast<const uint32_t*>(qs + k * 16);
            const uint32_t k_off = sbase + (warp * 8 + lrow) * 128;
            const uint32_t sw0 = (lmat ^ lrow) << 4, sw1 = ((lmat + 4) ^ lrow) << 4;
            float mx = -INFINITY;
            uint8_t* sdst = sgen + SM_ACT + g * ACT_PITCH + SEG_P + (warp * 8 + 2 * t) * 2;
#pragma unroll 1
            for (int it = 0; it < KT; it++) {
                ring.wait();
                const uint32_t tb = ring.slot * TILE_B + k_off;
                uint32_t b[16];
                ldsm4(tb + sw0, b); ldsm4(tb + sw1, b + 4); ldsm4(tb + 8192 + sw0, b + 8); ldsm4(tb + 8192 + sw1, b + 12);
                float c0[4] = {0.f, 0.f, 0.f, 0.f}, c1[4] = {0.f, 0.f, 0.f, 0.f};
#pragma unroll
                for (int k = 0; k < 8; k += 2) {
                    mma16816(c0, qa[2 * k], 0u, qa[2 * k + 1], 0u, b[2 * k], b[2 * k + 1]);
                    mma16816(c1, qa[2 * k + 2], 0u, qa[2 * k + 3], 0u, b[2 * k + 2], b[2 * k + 3]);
                }
                ring.release(lane);
                const float scale = 0.08838834764831845f;
                const uint32_t sp = pack_bf16(bf16r(c0[0] + c1[0]) * scale, bf16r(c0[1] + c1[1]) * scale);
                mx = fmaxf(mx, fmaxf(bf_lo(sp), bf_hi(sp)));
                if (lane < 16) *reinterpret_cast<uint32_t*>(sdst + it * 128) = sp;
            }
            mx = fmaxf(mx, __shfl_xor_sync(0xffffffffu, mx, 1));
            mx = fmaxf(mx, __shfl_xor_sync(0xffffffffu, mx, 2));
            if (lane < 16 && t == 0) reinterpret_cast<float*>(sgen + SM_WMAX)[warp * 4 + g] = mx;
            bar_sync(BAR_MMA, 256);
            const int head = warp >> 1;
            const float* wm = reinterpret_cast<const float*>(sgen + SM_WMAX) + head;
            float m = wm[0];
#pragma unroll
            for (int i = 1; i < 8; i++) m = fmaxf(m, wm[4 * i]);
            uint8_t* pp = sgen + SM_ACT + head * ACT_PITCH + SEG_P + (warp & 1) * 1024 + lane * 16;
            float l = 0.f;
#pragma unroll 1
            for (int h = 0; h < 2; h++) {
                const uint4 u = *reinterpret_cast<const uint4*>(pp + h * 512);
                uint32_t w[4] = {u.x, u.y, u.z, u.w};
#pragma unroll
                for (int i = 0; i < 4; i++) {
                    const float L2E = 1.4426950408889634f;
                    const float p0 = exp2f((bf_lo(w[i]) - m) * L2E), p1 = exp2f((bf_hi(w[i]) - m) * L2E);
                    l += p0 + p1;
                    w[i] = pack_bf16(p0, p1);
                }
                *reinterpret_cast<uint4*>(pp + h * 512) = make_uint4(w[0], w[1], w[2], w[3]);
            }
#pragma unroll
            for (int o = 16; o; o >>= 1) l += __shfl_xor_sync(0xffffffffu, l, o);
            if (lane == 0) reinterpret_cast<float*>(sgen + SM_LSUM)[warp] = l;
            bar_sync(BAR_MMA, 256);
            if ((warp & 1) && lane < 2) {
                const float* ls = reinterpret_cast<const float*>(sgen + SM_LSUM);
                st1(prm.arena + AR_XS + cta * 8 + head * 2 + lane, tagged(lane ? ls[warp - 1] + ls[warp] : m, tag));
            }
        }
        if ((sg == 2 || sg == 4) && !has_ffn) continue;
        const int i0 = (sg == 3) ? W1POS : (sg == 1) ? 0 : 32;
        const int i1 = (sg == 3) ? KT : (sg == 1) ? W1POS : (sg == 0) ? 34 : 33;
        const int seg = (sg == 0) ? SEG_XN + rlo * 256 : (sg == 2) ? SEG_XN + (cta & 7) * 128 : (sg == 4) ? SEG_H : SEG_P + i0 * 128;
        float* const pd = (sg == 0 ? prm.arena + AR_Q + cta * 512 : sg == 2 ? prm.arena + AR_H + (cta ^ 2) * 512 : myslot + AR_O) + pofs;
        uint32_t ba = b_off + seg;
        float c0[4], c1[4];
#pragma unroll
        for (int k = 0; k < 4; k++) { c0[k] = sg == 3 ? vs[k] : 0.f; c1[k] = sg == 3 ? vs[4 + k] : 0.f; }
        if (sg == 4) bar_sync(BAR_H, 384);
#pragma unroll 1
        for (int i = i0; i < i1; i++) {
            if (i == SGO) bar_arrive(BAR_SGO, N_SGO);
            if (i == CLRO) { st1(pd, 0u); st1(pd + 128, 0u); st1(pd + 1024, 0u); st1(pd + 1152, 0u); }
            if (i == CLRF && has_ffn) { st2(pub2 + AR_F, 0u, 0u); st2(pub2 + AR_F + 1024, 0u, 0u); }
            if (i == CLRS) { st2(pub2 + AR_S, 0u, 0u); st2(pub2 + AR_S + 1024, 0u, 0u); }
            uint32_t a[16], b[8];
            ldsm4(ba, b); ldsm4(ba + 64, b + 4);
            ring.wait();
            const uint32_t aa = a_off + ring.slot * TILE_B;
#pragma unroll
            for (int k = 0; k < 4; k++) ldsm4t(aa + k * 2048, a + 4 * k);
            mma16816(c0, a[0], a[1], a[2], a[3], b[0], b[1]);
            mma16816(c1, a[4], a[5], a[6], a[7], b[2], b[3]);
            mma16816(c0, a[8], a[9], a[10], a[11], b[4], b[5]);
            mma16816(c1, a[12], a[13], a[14], a[15], b[6], b[7]);
            ring.release(lane);
            ba += 128;
        }
        if (sg == 1) {
#pragma unroll
            for (int k = 0; k < 4; k++) { vs[k] = c0[k]; vs[4 + k] = c1[k]; }
            continue;
        }
        const uint32_t r0 = tagged(hi ? c0[2] + c1[2] : c0[0] + c1[0], tag), r1 = tagged(hi ? c0[3] + c1[3] : c0[1] + c1[1], tag);
        if (sg == 4) { st2(pub2 + AR_F, r0, r1); st2(pub2 + AR_F + 1024, r0, r1); }
        else {
            st1(pd, r0); st1(pd + 128, r1);
            if (sg == 3) { st1(pd + 1024, r0); st1(pd + 1152, r1); }
            if (sg != 2) bar_arrive(sg ? BAR_VGO : BAR_QGO, 384);
        }
    }
    bar_arrive(BAR_FGO, 288);
    {
        uint32_t a[8], b[16];
        float c[4][4];
#pragma unroll
        for (int k = 0; k < 4; k++) { c[k][0] = 0.f; c[k][1] = 0.f; c[k][2] = 0.f; c[k][3] = 0.f; }
        const uint32_t ap_off = sbase + (warp >> 2) * 4096 + a_lane;
        bar_sync(BAR_O, 384);
#pragma unroll
        for (int k = 0; k < 4; k++) ldsm4(b_off + SEG_O + k * 64, b + 4 * k);
#pragma unroll
        for (int q = 0; q < 4; q++) {
            const uint32_t bq = (q & 1) ? bar_half + (q >> 1) * 8 : ring.full + ring.slot * 8;
            const uint32_t pq = (q & 1) ? 0u : ring.phase;
            const uint32_t aa = ap_off + ring.slot * TILE_B + (q & 1) * (TILE_B / 2);
            if (q >= 2) mbar_spin(bq, pq); else mbar_wait(bq, pq);
            ldsm4t(aa, a); ldsm4t(aa + 2048, a + 4);
            mma16816(c[(2 * q) & 3], a[0], a[1], a[2], a[3], b[4 * q], b[4 * q + 1]);
            mma16816(c[(2 * q + 1) & 3], a[4], a[5], a[6], a[7], b[4 * q + 2], b[4 * q + 3]);
            if (q & 1) ring.next();
        }
        const float r0 = ((hi ? c[0][2] : c[0][0]) + (hi ? c[1][2] : c[1][0])) + ((hi ? c[2][2] : c[2][0]) + (hi ? c[3][2] : c[3][0]));
        const float r1 = ((hi ? c[0][3] : c[0][1]) + (hi ? c[1][3] : c[1][1])) + ((hi ? c[2][3] : c[2][1]) + (hi ? c[3][3] : c[3][1]));
        const uint32_t u0 = tagged(r0, tag), u1 = tagged(r1, tag);
        st2(pub2 + AR_S, u0, u1);
        st2(pub2 + AR_S + 1024, u0, u1);
        bar_arrive(BAR_SREL, N_SREL);
    }
}

typedef CUresult (*EncodeFn)(CUtensorMap*, CUtensorMapDataType, cuuint32_t, void*, const cuuint64_t*, const cuuint64_t*,
                             const cuuint32_t*, const cuuint32_t*, CUtensorMapInterleave, CUtensorMapSwizzle,
                             CUtensorMapL2promotion, CUtensorMapFloatOOBfill);

void make_map(EncodeFn enc, CUtensorMap* m, const void* base, uint64_t rows, uint64_t cols, uint32_t box_rows) {
    cuuint64_t dims[3] = {64, rows, cols / 64};
    cuuint64_t strides[2] = {cols * 2, 128};
    cuuint32_t box[3] = {64, box_rows, 2};
    cuuint32_t es[3] = {1, 1, 1};
    enc(m, CU_TENSOR_MAP_DATA_TYPE_BFLOAT16, 3, const_cast<void*>(base), dims, strides, box, es,
        CU_TENSOR_MAP_INTERLEAVE_NONE, CU_TENSOR_MAP_SWIZZLE_128B, CU_TENSOR_MAP_L2_PROMOTION_L2_256B,
        CU_TENSOR_MAP_FLOAT_OOB_FILL_NONE);
}

}

extern "C" void kernel_launch(void* const* d_in, const int* in_sizes, int n_in, void* d_out, int out_size) {
    (void)in_sizes; (void)n_in; (void)out_size;
    static EncodeFn enc = nullptr;
    static void* arena_ptr = nullptr;
    if (!enc) {
        void* fn = nullptr;
        cudaDriverEntryPointQueryResult qr;
        cudaGetDriverEntryPoint("cuTensorMapEncodeTiled", &fn, cudaEnableDefault, &qr);
        enc = (EncodeFn)fn;
        cudaGetSymbolAddress(&arena_ptr, g_arena);
        cudaFuncSetAttribute(fused_decode_kernel, cudaFuncAttributeMaxDynamicSharedMemorySize, SM_TOTAL + 1024);
    }
    Params prm;
    make_map(enc, &prm.m[0], d_in[3], 512, 4096, 64);
    make_map(enc, &prm.m[1], d_in[6], 512, 1792, 64);
    make_map(enc, &prm.m[2], d_in[1], 4ull * 8 * 16384, 128, 64);
    make_map(enc, &prm.m[3], d_in[2], 4ull * 8 * 16384, 128, 64);
    make_map(enc, &prm.m[4], d_in[7], 1792, 512, 64);
    make_map(enc, &prm.m[5], d_in[4], 4096, 512, 32);
    prm.raw[0] = (const char*)d_in[2];
    prm.raw[1] = (const char*)d_in[7];
    prm.raw[2] = (const char*)d_in[4];
    prm.x = (const __nv_bfloat16*)d_in[0];
    prm.out = (__nv_bfloat16*)d_out;
    prm.arena = (float*)(((uintptr_t)arena_ptr + 0x1fffffull) & ~0x1fffffull);
    fused_decode_kernel<<<NCTA, NTHREADS, SM_TOTAL + 1024>>>(prm);
}
```

```cpp
#include <cuda_runtime.h>
#include <cuda_bf16.h>
#include <cuda.h>
#include <stdint.h>

namespace {

constexpr int NCTA     = 128;
constexpr int NFFN     = 112;
constexpr int NSLOT    = 13;
constexpr int TILE_B   = 16384;
constexpr int KT       = 16;
constexpr int NS       = 3;
constexpr int NTHREADS = 448 + 32 * NS;

constexpr int TAU      = 657;
constexpr int LEAD     = 22;
constexpr int INFLIGHT = 8;
constexpr int TAILCAP  = 3;
constexpr int W1POS    = 6;
constexpr int QSLOT = 5;
constexpr int RGO   = 4;
constexpr int SGO   = 10;
constexpr int CLRO = 12, CLRF = 13, CLRS = 14;
constexpr unsigned SSTAG = 125;

constexpr int SEG_XN = 0;
constexpr int SEG_P  = 1024;
constexpr int SEG_H  = 3072;
constexpr int SEG_O  = 3200;
constexpr int SEG_Q  = 3456;
constexpr int ACT_PITCH = 3712 + 16;
constexpr int SM_ACT   = NSLOT * TILE_B;
constexpr int SM_WMAX  = SM_ACT + 4 * ACT_PITCH;
constexpr int SM_LSUM  = SM_WMAX + 128;
constexpr int SM_MISC  = SM_LSUM + 32;
constexpr int SM_BAR   = SM_MISC + 256;
constexpr int SM_TOTAL = SM_BAR + (2 * NSLOT + 2) * 8;
static_assert(SM_TOTAL + 1024 <= 232448, "smem");

constexpr int BAR_MMA = 1, BAR_XN = 2, BAR_Q = 3, BAR_H = 4, BAR_O = 5, BAR_VGO = 6, BAR_QGO = 7, BAR_SGO = 8,
              BAR_FGO = 9, BAR_SREL = 10, BAR_RGO = 11;
constexpr int N_SGO = 416 + 32 * NS, N_SREL = 256 + 32 * NS;

__device__ __align__(4096) float g_arena[1 << 20];
constexpr int AR_O = 0, AR_F = 131072, AR_S = 262144, AR_Q = 393216, AR_H = 458752;
constexpr int AR_XS = AR_F + 62 * 2048;
constexpr int AR_EPOCH = AR_XS + 2048;
constexpr uint32_t HOME_MASK = (1u << 12) | (1u << 13) | (1u << 16) | (1u << 17) | (1u << 19);

struct Params {
    CUtensorMap m[6];
    const char* raw[3];
    const __nv_bfloat16* x;
    __nv_bfloat16* out;
    float* arena;
};

constexpr unsigned SPIN_LIMIT = 1u << 20;

__device__ __forceinline__ int phase_key(int cta) { return (((cta >> 2) * 13) & 31) * 4 + (cta & 3); }
__device__ __forceinline__ int slot_off(int producer) { return (producer >> 1) * 2048 + (producer & 1) * 512; }
__device__ __forceinline__ uint32_t parity(int off) { return __popc(((uint32_t)off << 2) & HOME_MASK) & 1u; }
__device__ __forceinline__ int pick(int off, uint32_t side) { return off + (int)((parity(off) ^ side) << 10); }

__device__ __forceinline__ void mbar_init(uint32_t bar, uint32_t cnt) {
    asm volatile("mbarrier.init.shared::cta.b64 [%0], %1;" :: "r"(bar), "r"(cnt) : "memory");
}
__device__ __forceinline__ void mbar_expect_tx(uint32_t bar, uint32_t bytes) {
    asm volatile("mbarrier.arrive.expect_tx.shared::cta.b64 _, [%0], %1;" :: "r"(bar), "r"(bytes) : "memory");
}
__device__ __forceinline__ void mbar_arrive(uint32_t bar) {
    asm volatile("mbarrier.arrive.shared::cta.b64 _, [%0];" :: "r"(bar) : "memory");
}
__device__ __forceinline__ bool mbar_test(uint32_t bar, uint32_t par) {
    uint32_t ok;
    asm volatile("{\n .reg .pred p;\n mbarrier.test_wait.parity.shared::cta.b64 p, [%1], %2;\n selp.u32 %0, 1, 0, p;\n}"
                 : "=r"(ok) : "r"(bar), "r"(par) : "memory");
    return ok;
}
__device__ __forceinline__ void mbar_wait(uint32_t bar, uint32_t par) {
    uint32_t ok, it = 0;
    while (true) {
        asm volatile("{\n .reg .pred p;\n mbarrier.try_wait.parity.shared::cta.b64 p, [%1], %2, %3;\n selp.u32 %0, 1, 0, p;\n}"
                     : "=r"(ok) : "r"(bar), "r"(par), "r"(10000) : "memory");
        if (ok) break;
        if (++it > SPIN_LIMIT) __trap();
    }
}
__device__ __forceinline__ void mbar_spin(uint32_t bar, uint32_t par) {
    uint32_t ok, it = 0;
    while (true) {
        asm volatile("{\n .reg .pred p;\n mbarrier.try_wait.parity.shared::cta.b64 p, [%1], %2;\n selp.u32 %0, 1, 0, p;\n}"
                     : "=r"(ok) : "r"(bar), "r"(par) : "memory");
        if (ok) break;
        if (++it > 16 * SPIN_LIMIT) __trap();
    }
}
__device__ __forceinline__ void tma_tile(uint32_t dst, const CUtensorMap* tm, int row, int half, uint32_t bar) {
    asm volatile("cp.async.bulk.tensor.3d.shared::cluster.global.mbarrier::complete_tx::bytes.L2::cache_hint [%0], [%1, {%3, %4, %5}], [%2], %6;"
                 :: "r"(dst), "l"(tm), "r"(bar), "r"(0), "r"(row), "r"(half), "l"(0x12F0000000000000ull) : "memory");
}
__device__ __forceinline__ void ldsm4(uint32_t addr, uint32_t* r) {
    asm volatile("ldmatrix.sync.aligned.m8n8.x4.shared.b16 {%0,%1,%2,%3}, [%4];"
                 : "=r"(r[0]), "=r"(r[1]), "=r"(r[2]), "=r"(r[3]) : "r"(addr) : "memory");
}
__device__ __forceinline__ void ldsm4t(uint32_t addr, uint32_t* r) {
    asm volatile("ldmatrix.sync.aligned.m8n8.x4.trans.shared.b16 {%0,%1,%2,%3}, [%4];"
                 : "=r"(r[0]), "=r"(r[1]), "=r"(r[2]), "=r"(r[3]) : "r"(addr) : "memory");
}
__device__ __forceinline__ void mma16816(float (&c)[4], uint32_t a0, uint32_t a1, uint32_t a2, uint32_t a3,
                                         uint32_t b0, uint32_t b1) {
    asm volatile("mma.sync.aligned.m16n8k16.row.col.f32.bf16.bf16.f32 {%0,%1,%2,%3}, {%4,%5,%6,%7}, {%8,%9}, {%0,%1,%2,%3};"
                 : "+f"(c[0]), "+f"(c[1]), "+f"(c[2]), "+f"(c[3])
                 : "r"(a0), "r"(a1), "r"(a2), "r"(a3), "r"(b0), "r"(b1));
}
__device__ __forceinline__ void bar_sync(int id, int n) { asm volatile("bar.sync %0, %1;" :: "r"(id), "r"(n) : "memory"); }
__device__ __forceinline__ void bar_arrive(int id, int n) { asm volatile("bar.arrive %0, %1;" :: "r"(id), "r"(n) : "memory"); }
__device__ __forceinline__ unsigned gtime32() { unsigned t; asm volatile("mov.u32 %0, %%globaltimer_lo;" : "=r"(t)); return t; }
__device__ __forceinline__ unsigned clock32() { unsigned t; asm volatile("mov.u32 %0, %%clock;" : "=r"(t)); return t; }
__device__ __forceinline__ void delay(unsigned clocks) { const unsigned c0 = clock32(); while (clock32() - c0 < clocks) {} }

__device__ __forceinline__ float bf16r(float v) {
    uint32_t d; asm("cvt.rn.bf16x2.f32 %0, %1, %2;" : "=r"(d) : "f"(v), "f"(0.f));
    return __uint_as_float(d);
}
__device__ __forceinline__ uint32_t pack_bf16(float lo, float hi) {
    uint32_t d; asm("cvt.rn.bf16x2.f32 %0, %1, %2;" : "=r"(d) : "f"(hi), "f"(lo));
    return d;
}
__device__ __forceinline__ float bf_lo(uint32_t u) { return __uint_as_float(u << 16); }
__device__ __forceinline__ float bf_hi(uint32_t u) { return __uint_as_float(u & 0xffff0000u); }
__device__ __forceinline__ float asf(uint32_t u) { return __uint_as_float(u); }

__device__ __forceinline__ uint32_t tagged(float v, uint32_t tag) { return (__float_as_uint(v) & ~3u) | tag; }
__device__ __forceinline__ void st1(float* p, uint32_t u) {
    asm volatile("st.relaxed.gpu.global.u32 [%0], %1;" :: "l"(p), "r"(u) : "memory");
}
__device__ __forceinline__ void st2(float* p, uint32_t u0, uint32_t u1) {
    asm volatile("st.relaxed.gpu.global.v2.u32 [%0], {%1, %2};" :: "l"(p), "r"(u0), "r"(u1) : "memory");
}
__device__ __forceinline__ uint4 ld4(const float* p) {
    uint4 v;
    asm volatile("ld.relaxed.gpu.global.v4.u32 {%0,%1,%2,%3}, [%4];" : "=r"(v.x), "=r"(v.y), "=r"(v.z), "=r"(v.w) : "l"(p) : "memory");
    return v;
}
__device__ __forceinline__ uint32_t badbits(const uint4& v, uint32_t tag) {
    uint32_t a, b;
    asm("lop3.b32 %0, %1, %2, %3, 0x7e;" : "=r"(a) : "r"(v.x), "r"(tag), "r"(v.y));
    asm("lop3.b32 %0, %1, %2, %3, 0x7e;" : "=r"(b) : "r"(v.z), "r"(tag), "r"(v.w));
    return a | b;
}
__device__ __forceinline__ void gather4(uint4 (&v)[4], const float* p0, const float* p1, const float* p2, const float* p3, uint32_t tag) {
    v[0] = ld4(p0); v[1] = ld4(p1); v[2] = ld4(p2); v[3] = ld4(p3);
    unsigned it = 0;
    while (true) {
        const uint32_t b0 = badbits(v[0], tag), b1 = badbits(v[1], tag), b2 = badbits(v[2], tag), b3 = badbits(v[3], tag);
        if (!__any_sync(0xffffffffu, ((b0 | b1) | (b2 | b3)) & 3u)) break;
        if (b0 & 3u) v[0] = ld4(p0);
        if (b1 & 3u) v[1] = ld4(p1);
        if (b2 & 3u) v[2] = ld4(p2);
        if (b3 & 3u) v[3] = ld4(p3);
        if (++it > SPIN_LIMIT) __trap();
    }
}
__device__ __forceinline__ float4 sum4(const uint4 (&v)[4]) {
    return make_float4((asf(v[0].x) + asf(v[1].x)) + (asf(v[2].x) + asf(v[3].x)), (asf(v[0].y) + asf(v[1].y)) + (asf(v[2].y) + asf(v[3].y)),
                       (asf(v[0].z) + asf(v[1].z)) + (asf(v[2].z) + asf(v[3].z)), (asf(v[0].w) + asf(v[1].w)) + (asf(v[2].w) + asf(v[3].w)));
}
__device__ __forceinline__ uint32_t near_side(volatile uint32_t* misc) {
    const uint32_t m0 = min(min(misc[40], misc[42]), min(misc[44], misc[46]));
    const uint32_t m1 = min(min(misc[41], misc[43]), min(misc[45], misc[47]));
    return m1 < m0;
}

struct Ring {
    uint32_t full, empty;
    int slot; uint32_t phase;
    __device__ __forceinline__ void wait() { mbar_wait(full + slot * 8, phase); }
    __device__ __forceinline__ void next() { if (++slot == NSLOT) { slot = 0; phase ^= 1; } }
    __device__ __forceinline__ void release(int lane) {
        __syncwarp();
        if (lane == 0) mbar_arrive(empty + slot * 8);
        next();
    }
};

__global__ void __launch_bounds__(NTHREADS, 1)
fused_decode_kernel(const __grid_constant__ Params prm) {
    extern __shared__ uint8_t smem_raw[];
    const uint32_t sbase = ((uint32_t)__cvta_generic_to_shared(smem_raw) + 1023u) & ~1023u;
    uint8_t* sgen = smem_raw + (sbase - (uint32_t)__cvta_generic_to_shared(smem_raw));
    const int cta = blockIdx.x;
    const int hkv = cta >> 4, rhi = (cta >> 2) & 3, rlo = cta & 3;
    const bool has_w1 = cta < NFFN;
    const uint32_t bar_full = sbase + SM_BAR, bar_empty = bar_full + NSLOT * 8, bar_half = bar_empty + NSLOT * 8;

    if (threadIdx.x - 1u < 31u) return;
    if (threadIdx.x == 0) {
        const unsigned t0 = gtime32();
        mbar_init(bar_full, 1);
        asm volatile("fence.mbarrier_init.release.cluster;" ::: "memory");
        mbar_expect_tx(bar_full, TILE_B);
        tma_tile(sbase, &prm.m[0], rhi * 128, (hkv * 4 + rlo) * 2, bar_full);
#pragma unroll
        for (int i = 1; i < 2 * NSLOT + 2; i++) mbar_init(bar_full + i * 8, (i < NSLOT || i >= 2 * NSLOT) ? 1 : 8);
        asm volatile("fence.mbarrier_init.release.cluster;" ::: "memory");
        volatile uint32_t* prole = reinterpret_cast<volatile uint32_t*>(sgen + SM_MISC) + 34;
        *prole = 0xffffffffu;
        asm volatile("barrier.arrive %0, %1;" :: "n"(BAR_XN), "n"(448) : "memory");
        const int kvrow = (rhi * 8 + hkv) * 16384 + 12288 + rlo * 64;
        const int toff = ((phase_key(cta) >> 2) * TAU) / 32 - (LEAD * TAU) / 16;
        constexpr int P_W1 = 18 + W1POS, P_W2 = 35, P_END = 38;
        int slot = 1; uint32_t eph = 1;
        int fslot = 0; uint32_t fph = 0;
        int landed = 0, issued = 1;
        uint32_t role = 0;
#pragma unroll 1
        for (int v = 1; v < P_END; v++) {
            if (v == 31) {
                unsigned it = 0;
                while ((role = *prole) == 0xffffffffu) { if (++it > 16 * SPIN_LIMIT) __trap(); }
            }
            const int rh = role & 31, rc = role >> 5;
            const bool has_w2 = rh < 28;
            int mi, row, half;
            if (v == 1)          { mi = 0; row = rhi * 128 + 64; half = (hkv * 4 + rlo) * 2; }
            else if (v == P_W1)  { mi = 1; row = ((cta >> 1) & 7) * 64; half = (hkv * 2 + (cta & 1)) * 2; }
            else if (v < P_W2)   { const int j = v - 2 - (v > P_W1); mi = 2 + (j >> 4); row = kvrow + (j & 15) * 256; half = 0; }
            else if (v == P_W2)  { mi = 4; row = rh * 64; half = rc * 2; }
            else                 { mi = 5; row = rh * 128 + (v - P_W2 - 1) * 64; half = rc * 2; }
            if (v < 6) asm volatile("prefetch.tensormap [%0];" :: "l"(&prm.m[v]) : "memory");
            if (v == 10) asm volatile("cp.async.bulk.prefetch.L2.global [%0], 128;" :: "l"(prm.raw[0] + (size_t)kvrow * 256) : "memory");
            if (v == 31) {
                if (has_w2) asm volatile("cp.async.bulk.prefetch.L2.global [%0], 128;" :: "l"(prm.raw[1] + rh * 65536 + rc * 256) : "memory");
                asm volatile("cp.async.bulk.prefetch.L2.global [%0], 128;" :: "l"(prm.raw[2] + rh * 131072 + rc * 256) : "memory");
            }
            if ((v == P_W1 && !has_w1) || (v == P_W2 && !has_w2)) continue;
            const int need = issued + 1 - (v >= P_W2 ? TAILCAP : INFLIGHT);
            while (landed < need) {
                mbar_wait(bar_full + fslot * 8, fph);
                if (++fslot == NSLOT) { fslot = 0; fph ^= 1; }
                landed++;
            }
            if (issued >= NSLOT) mbar_wait(bar_empty + slot * 8, eph);
            {
                const int due = (v - (!has_w2 && v > P_W2)) * TAU + toff;
                int s2 = slot - 2; uint32_t par = eph ^ 1;
                if (s2 < 0) { s2 += NSLOT; par ^= 1; }
                while ((int)(gtime32() - t0) < due) {
                    if (v > 4 && mbar_test(bar_full + s2 * 8, par)) break;
                }
            }
            const uint32_t dst = sbase + slot * TILE_B, bf = bar_full + slot * 8;
            if (v > P_W2) {
                const uint32_t bh = bar_half + (v - P_W2 - 1) * 8;
                mbar_expect_tx(bf, TILE_B / 2);
                tma_tile(dst, &prm.m[5], row, half, bf);
                mbar_expect_tx(bh, TILE_B / 2);
                tma_tile(dst + TILE_B / 2, &prm.m[5], row + 32, half, bh);
            } else {
                mbar_expect_tx(bf, TILE_B);
                tma_tile(dst, &prm.m[mi], row, half, bf);
            }
            if (++slot == NSLOT) { slot = 0; eph ^= 1; }
            issued++;
        }
    }
    int tix;
    asm volatile("mov.u32 %0, %%tid.x;" : "=r"(tix));
    if (tix == 0) return;
    const int lane = tix & 31;
    const int wix = __shfl_sync(0xffffffffu, tix >> 5, 0);
    volatile uint32_t* misc = reinterpret_cast<volatile uint32_t*>(sgen + SM_MISC);

    if (wix < 5) {
        const int gw = wix - 1;
        {
            const uint4* xr = reinterpret_cast<const uint4*>(prm.x + gw * 512);
            const uint4 u0 = __ldg(xr + lane), u1 = __ldg(xr + 32 + lane);
            const uint32_t w[8] = {u0.x, u0.y, u0.z, u0.w, u1.x, u1.y, u1.z, u1.w};
            float s = 0.f;
#pragma unroll
            for (int i = 0; i < 8; i++) s += bf_lo(w[i]) + bf_hi(w[i]);
#pragma unroll
            for (int o = 16; o; o >>= 1) s += __shfl_xor_sync(0xffffffffu, s, o);
            const float mean = s * (1.f / 512.f);
            float vs = 0.f;
#pragma unroll
            for (int i = 0; i < 8; i++) { const float d0 = bf_lo(w[i]) - mean, d1 = bf_hi(w[i]) - mean; vs += d0 * d0 + d1 * d1; }
#pragma unroll
            for (int o = 16; o; o >>= 1) vs += __shfl_xor_sync(0xffffffffu, vs, o);
            const float mb = bf16r(mean);
            const float den = bf16r(sqrtf(bf16r(bf16r(vs * (1.f / 512.f)) + 1e-5f)));
#pragma unroll 1
            for (int h = 0; h < 2; h++) {
                const uint4 u = h ? u1 : u0;
                const uint32_t uu[4] = {u.x, u.y, u.z, u.w};
                uint32_t r[4];
#pragma unroll
                for (int i = 0; i < 4; i++)
                    r[i] = pack_bf16(__fdiv_rn(bf16r(bf_lo(uu[i]) - mb), den), __fdiv_rn(bf16r(bf_hi(uu[i]) - mb), den));
                *reinterpret_cast<uint4*>(sgen + SM_ACT + gw * ACT_PITCH + SEG_XN + h * 512 + lane * 16) = make_uint4(r[0], r[1], r[2], r[3]);
            }
        }
        bar_arrive(BAR_XN, 448);
        float wv[4] = {1.f, 1.f, 1.f, 1.f};
        const float* pa = prm.arena + AR_Q + (hkv * 16 + gw * 4) * 512 + rhi * 128 + lane * 4;
        const float* pb = pa + 1024;
#pragma unroll 1
        for (int r = 0; r < 2; r++) {
            bar_sync(r ? BAR_VGO : BAR_QGO, 384);
            const uint32_t tag = misc[32];
            if (r == 0) mbar_wait(bar_full + QSLOT * 8, 0);
            {
                uint4 v[4];
                gather4(v, pa, pa + 512, pb, pb + 512, tag);
                const float o0 = fmaf(wv[0], asf(v[0].x), wv[1] * asf(v[1].x)) + fmaf(wv[2], asf(v[2].x), wv[3] * asf(v[3].x));
                const float o1 = fmaf(wv[0], asf(v[0].y), wv[1] * asf(v[1].y)) + fmaf(wv[2], asf(v[2].y), wv[3] * asf(v[3].y));
                const float o2 = fmaf(wv[0], asf(v[0].z), wv[1] * asf(v[1].z)) + fmaf(wv[2], asf(v[2].z), wv[3] * asf(v[3].z));
                const float o3 = fmaf(wv[0], asf(v[0].w), wv[1] * asf(v[1].w)) + fmaf(wv[2], asf(v[2].w), wv[3] * asf(v[3].w));
                *reinterpret_cast<uint2*>(sgen + SM_ACT + gw * ACT_PITCH + (r ? SEG_O : SEG_Q) + lane * 8) =
                    make_uint2(pack_bf16(o0, o1), pack_bf16(o2, o3));
                bar_arrive(r ? BAR_O : BAR_Q, 384);
            }
            if (r) break;
            bar_sync(BAR_SGO, N_SGO);
            const int rh = misc[34] & 31;
            {
                const uint32_t side = near_side(misc);
                const int o = AR_O + slot_off((rh >> 2) * 16 + gw * 4) + (rh & 3) * 128 + lane * 4;
                pa = prm.arena + pick(o, side);
                pb = prm.arena + pick(o + 2048, side);
            }
            if (rh < 28) {
                const int rg = rh;
                const float* ph = prm.arena + AR_H + ((rg >> 1) * 8 + (lane >> 4) * 4) * 512 + gw * 128 + (rg & 1) * 64 + (lane & 15) * 4;
                uint4 v[4];
                gather4(v, ph, ph + 512, ph + 1024, ph + 1536, tag);
                float4 h = sum4(v);
                h.x += __shfl_xor_sync(0xffffffffu, h.x, 16); h.y += __shfl_xor_sync(0xffffffffu, h.y, 16);
                h.z += __shfl_xor_sync(0xffffffffu, h.z, 16); h.w += __shfl_xor_sync(0xffffffffu, h.w, 16);
                if (lane < 16)
                    *reinterpret_cast<uint2*>(sgen + SM_ACT + gw * ACT_PITCH + SEG_H + lane * 8) =
                        make_uint2(pack_bf16(fmaxf(h.x, 0.f), fmaxf(h.y, 0.f)), pack_bf16(fmaxf(h.z, 0.f), fmaxf(h.w, 0.f)));
                bar_arrive(BAR_H, 384);
            }
            {
                const float* ps = prm.arena + AR_XS + ((rh >> 2) * 16 + gw * 4 + (lane & 3)) * 8 + (rh & 2) * 2;
                uint4 v = ld4(ps);
                unsigned it = 0;
                while (__any_sync(0xffffffffu, badbits(v, tag) & 3u)) { v = ld4(ps); if (++it > SPIN_LIMIT) __trap(); }
                const float m = bf_hi((rh & 1) ? v.z : v.x);
                const float l = asf((rh & 1) ? v.w : v.y);
                float M = fmaxf(m, __shfl_xor_sync(0xffffffffu, m, 1));
                M = fmaxf(M, __shfl_xor_sync(0xffffffffu, M, 2));
                const float e = __expf(m - M);
                float L = e * l;
                L += __shfl_xor_sync(0xffffffffu, L, 1);
                L += __shfl_xor_sync(0xffffffffu, L, 2);
                const float wgt = e / L;
#pragma unroll
                for (int i = 0; i < 4; i++) wv[i] = __shfl_sync(0xffffffffu, wgt, i);
            }
        }
        return;
    }

    if (wix < 6 + NS) {
        const bool is_s = wix >= 6;
        if (wix == 6) { misc[lane] = 0xffffffffu; misc[33] = 0u; }
        if (wix == 5) {
            if (lane == 0) {
                unsigned epoch;
                asm volatile("ld.relaxed.gpu.global.u32 %0, [%1];" : "=r"(epoch) : "l"(prm.arena + AR_EPOCH) : "memory");
                misc[32] = epoch + 1;
            }
            __syncwarp();
            bar_arrive(BAR_XN, 448);
            bar_sync(BAR_RGO, 288);
            const uint32_t tg = misc[32];
            const float* pw = prm.arena + AR_XS + lane * 8;
            uint4 sw[4];
            gather4(sw, pw, pw + 256, pw + 512, pw + 768, tg);
            uint32_t n1 = 0, below = 0;
#pragma unroll
            for (int i = 0; i < 4; i++) {
                const uint32_t ones = __ballot_sync(0xffffffffu, sw[i].x & 4u);
                n1 += __popc(ones);
                below += __popc(ones & __ballot_sync(0xffffffffu, phase_key(i * 32 + lane) < phase_key(cta)));
            }
            if (lane == 0) {
                misc[35] = NCTA - n1;
                const uint32_t rank = near_side(misc) ? NCTA - n1 + below : phase_key(cta) - below;
                misc[34] = ((rank >> 6) * 2 + (rank & 1)) * 32 + ((rank & 63) >> 1);
            }
        }
        bar_sync(BAR_SGO, N_SGO);
        const uint32_t side = near_side(misc);
        const uint32_t tag = misc[32];
        const int role = misc[34];
        const int p = lane >> 2;
        const int o = slot_off((role & ~31) + p) + (role & 31) * 16 + (lane & 3) * 4 + (is_s ? AR_S : AR_F);
        const float* s0 = prm.arena + pick(o, side);
        const float* s1 = prm.arena + pick(o + 8192, side);
        const float* s2 = prm.arena + pick(o + 16384, side);
        const float* s3 = prm.arena + pick(o + 24576, side);
        const bool u16 = lane & 16, u8 = lane & 8;
        uint4 v[4];
        if (!is_s) {
            const bool skip3 = p >= 4;
            if (skip3) s3 = s0;
            bar_sync(BAR_FGO, 288);
            gather4(v, s0, s1, s2, s3, tag);
            if (skip3) v[3] = make_uint4(0u, 0u, 0u, 0u);
            const float4 a = sum4(v);
            const float e0 = (u16 ? a.z : a.x) + __shfl_xor_sync(0xffffffffu, u16 ? a.x : a.z, 16);
            const float e1 = (u16 ? a.w : a.y) + __shfl_xor_sync(0xffffffffu, u16 ? a.y : a.w, 16);
            float c = (u8 ? e1 : e0) + __shfl_xor_sync(0xffffffffu, u8 ? e0 : e1, 8);
            c += __shfl_xor_sync(0xffffffffu, c, 4);
            const float f = bf16r(c);
            misc[lane] = __float_as_uint(bf16r(__fdividef(f, 1.f + __expf(-f))));
        } else {
            const int oidx = (lane >> 3) * 512 + role * 4 + (lane & 3);
            const float xfin = __bfloat162float(prm.x[oidx]);
            const unsigned long long optr = __shfl_sync(0xffffffffu, (unsigned long long)(prm.out + oidx), lane);
            const uint32_t zero = tag >> 8;
            const uint32_t gaddr = sbase + SM_MISC + lane * 4;
            const bool bump = (cta | lane | zero) == 0;
            bar_sync(BAR_SREL, N_SREL);
            if (wix > 6) delay((wix - 6) * SSTAG);
            unsigned it = 0;
            uint32_t gate, done, b0 = 1, b1 = 1, b2 = 1, b3 = 1;
            float k0, k1, t0, t1;
            while (true) {
                if (b0 & 3u) v[0] = ld4(s0);
                if (b1 & 3u) v[1] = ld4(s1);
                if (b2 & 3u) v[2] = ld4(s2);
                if (b3 & 3u) v[3] = ld4(s3);
                b0 = badbits(v[0], tag); b1 = badbits(v[1], tag); b2 = badbits(v[2], tag); b3 = badbits(v[3], tag);
                const uint32_t bad = (b0 | b1) | (b2 | b3);
                asm volatile("ld.volatile.shared.u32 %0, [%1];" : "=r"(done) : "r"(sbase + SM_MISC + 33 * 4 + (bad & zero)) : "memory");
                asm volatile("ld.volatile.shared.u32 %0, [%1];" : "=r"(gate) : "r"(gaddr + (bad & zero)) : "memory");
                const float4 a = sum4(v);
                k0 = u16 ? a.z : a.x; k1 = u16 ? a.w : a.y;
                t0 = __shfl_xor_sync(0xffffffffu, u16 ? a.x : a.z, 16);
                t1 = __shfl_xor_sync(0xffffffffu, u16 ? a.y : a.w, 16);
                const bool again = __any_sync(0xffffffffu, bad & 3u);
                asm volatile("{\n .reg .pred p;\n setp.eq.u32 p, %1, 0;\n @p st.volatile.shared.u32 [%0], %2;\n}"
                             :: "r"(sbase + SM_MISC + 33 * 4), "r"((uint32_t)again), "r"(tag) : "memory");
                if (!again) break;
                if (done) return;
                if (++it > SPIN_LIMIT) __trap();
            }
            const float e0 = k0 + t0, e1 = k1 + t1;
            float c = (u8 ? e1 : e0) + __shfl_xor_sync(0xffffffffu, u8 ? e0 : e1, 8);
            if (done) return;
            c += __shfl_xor_sync(0xffffffffu, c, 4);
            it = 0;
            while (gate == 0xffffffffu) { gate = misc[lane]; if (++it > 16 * SPIN_LIMIT) __trap(); }
            const float res = xfin + bf16r(bf16r(c) * asf(gate));
            asm volatile("st.global.u16 [%0], %1;" :: "l"(optr), "h"((unsigned short)pack_bf16(res, 0.f)) : "memory");
            if (bump) *reinterpret_cast<unsigned*>(prm.arena + AR_EPOCH) = (tag == 3) ? 0u : tag;
        }
        return;
    }

    const int warp = wix - (6 + NS);
    const int qslot = hkv * 16 + rlo * 4 + rhi, hslot = (hkv * 2 + (cta & 1)) * 8 + ((cta >> 1) & 7);
    {
        float* pr = prm.arena + pick(AR_O + slot_off(cta) + (warp >> 1) * 128, warp & 1);
        if (lane < 4) st2(pr + lane * 2, 0u, 0u);
        bar_sync(BAR_MMA, 256);
        delay(300);
        if (lane == 0) {
            uint32_t v, c1;
            const uint32_t c0 = clock32();
            asm volatile("atom.relaxed.gpu.global.add.u32 %0, [%1], 4;" : "=r"(v) : "l"(pr) : "memory");
            asm volatile("{\n .reg .pred p;\n setp.ne.u32 p, %1, 1;\n mov.u32 %0, 0;\n @p mov.u32 %0, %%clock;\n}" : "=r"(c1) : "r"(v));
            misc[40 + warp] = c1 - c0;
        }
        __syncwarp();
    }
    const int g = lane >> 2, t = lane & 3;
    Ring ring{bar_full, bar_empty, 0, 0u};
    const int lrow = lane & 7, lmat = lane >> 3;
    const uint32_t a_lane = (lrow + ((lmat >> 1) << 3)) * 128 + ((((warp & 3) * 2 + (lmat & 1)) ^ lrow) << 4);
    const uint32_t a_off = sbase + (warp >> 2) * 8192 + a_lane;
    const uint32_t b_off = sbase + SM_ACT + (lane & 3) * ACT_PITCH + lmat * 16;
    const bool hi = t >= 2;
    const int pofs = (t & 1) * 256 + warp * 16 + g + (t >> 1) * 8;
    float* const myslot = prm.arena + slot_off(cta);
    float* pubf = nullptr; float* pubs = nullptr;
    bool has_w2 = false;
    bar_sync(BAR_XN, 448);
    const uint32_t tag = misc[32];

    float vs[8] = {0.f, 0.f, 0.f, 0.f, 0.f, 0.f, 0.f, 0.f};
#pragma unroll 1
    for (int sg = 0; sg < 5; sg++) {
        if (sg == 1) {
            if (warp == 0 && lane < 4) st2(prm.arena + AR_XS + cta * 8 + lane * 2, 0u, 0u);
            bar_sync(BAR_Q, 384);
            uint32_t qa[16];
            const uint8_t* qs = sgen + SM_ACT + (g & 3) * ACT_PITCH + SEG_Q + t * 4;
#pragma unroll
            for (int k = 0; k < 16; k++) qa[k] = *reinterpret_cast<const uint32_t*>(qs + k * 16);
            const uint32_t k_off = sbase + (warp * 8 + lrow) * 128;
            const uint32_t sw0 = (lmat ^ lrow) << 4, sw1 = ((lmat + 4) ^ lrow) << 4;
            float mx = -INFINITY;
            uint8_t* sdst = sgen + SM_ACT + g * ACT_PITCH + SEG_P + (warp * 8 + 2 * t) * 2;
#pragma unroll 1
            for (int it = 0; it < KT; it++) {
                ring.wait();
                const uint32_t tb = ring.slot * TILE_B + k_off;
                uint32_t b[16];
                ldsm4(tb + sw0, b); ldsm4(tb + sw1, b + 4); ldsm4(tb + 8192 + sw0, b + 8); ldsm4(tb + 8192 + sw1, b + 12);
                float c0[4] = {0.f, 0.f, 0.f, 0.f}, c1[4] = {0.f, 0.f, 0.f, 0.f};
#pragma unroll
                for (int k = 0; k < 8; k += 2) {
                    mma16816(c0, qa[2 * k], 0u, qa[2 * k + 1], 0u, b[2 * k], b[2 * k + 1]);
                    mma16816(c1, qa[2 * k + 2], 0u, qa[2 * k + 3], 0u, b[2 * k + 2], b[2 * k + 3]);
                }
                ring.release(lane);
                const float scale = 0.08838834764831845f;
                const uint32_t sp = pack_bf16(bf16r(c0[0] + c1[0]) * scale, bf16r(c0[1] + c1[1]) * scale);
                mx = fmaxf(mx, fmaxf(bf_lo(sp), bf_hi(sp)));
                if (lane < 16) *reinterpret_cast<uint32_t*>(sdst + it * 128) = sp;
            }
            mx = fmaxf(mx, __shfl_xor_sync(0xffffffffu, mx, 1));
            mx = fmaxf(mx, __shfl_xor_sync(0xffffffffu, mx, 2));
            if (lane < 16 && t == 0) reinterpret_cast<float*>(sgen + SM_WMAX)[warp * 4 + g] = mx;
            bar_sync(BAR_MMA, 256);
            const int head = warp >> 1;
            const float* wm = reinterpret_cast<const float*>(sgen + SM_WMAX) + head;
            float m = wm[0];
#pragma unroll
            for (int i = 1; i < 8; i++) m = fmaxf(m, wm[4 * i]);
            uint8_t* pp = sgen + SM_ACT + head * ACT_PITCH + SEG_P + (warp & 1) * 1024 + lane * 16;
            float l = 0.f;
#pragma unroll 1
            for (int h = 0; h < 2; h++) {
                const uint4 u = *reinterpret_cast<const uint4*>(pp + h * 512);
                uint32_t w[4] = {u.x, u.y, u.z, u.w};
#pragma unroll
                for (int i = 0; i < 4; i++) {
                    const float L2E = 1.4426950408889634f;
                    const float p0 = exp2f((bf_lo(w[i]) - m) * L2E), p1 = exp2f((bf_hi(w[i]) - m) * L2E);
                    l += p0 + p1;
                    w[i] = pack_bf16(p0, p1);
                }
                *reinterpret_cast<uint4*>(pp + h * 512) = make_uint4(w[0], w[1], w[2], w[3]);
            }
#pragma unroll
            for (int o = 16; o; o >>= 1) l += __shfl_xor_sync(0xffffffffu, l, o);
            if (lane == 0) reinterpret_cast<float*>(sgen + SM_LSUM)[warp] = l;
            bar_sync(BAR_MMA, 256);
            if ((warp & 1) && lane < 2) {
                const float* ls = reinterpret_cast<const float*>(sgen + SM_LSUM);
                st1(prm.arena + AR_XS + cta * 8 + head * 2 + lane, lane ? tagged(ls[warp - 1] + ls[warp], tag) : (__float_as_uint(m) | tag | (near_side(misc) << 2)));
            }
        }
        if ((sg == 2 && !has_w1) || (sg == 4 && !has_w2)) continue;
        const int i0 = (sg == 3) ? W1POS : (sg == 1) ? 0 : 32;
        const int i1 = (sg == 3) ? KT : (sg == 1) ? W1POS : (sg == 0) ? 34 : 33;
        const int seg = (sg == 0) ? SEG_XN + rhi * 256 : (sg == 2) ? SEG_XN + ((cta >> 1) & 7) * 128 : (sg == 4) ? SEG_H : SEG_P + i0 * 128;
        float* const pd = (sg == 0 ? prm.arena + AR_Q + qslot * 512 : sg == 2 ? prm.arena + AR_H + hslot * 512 : myslot + AR_O) + pofs;
        uint32_t ba = b_off + seg;
        float c0[4], c1[4];
#pragma unroll
        for (int k = 0; k < 4; k++) { c0[k] = sg == 3 ? vs[k] : 0.f; c1[k] = sg == 3 ? vs[4 + k] : 0.f; }
        if (sg == 4) bar_sync(BAR_H, 384);
#pragma unroll 1
        for (int i = i0; i < i1; i++) {
            if (i == RGO) bar_arrive(BAR_RGO, 288);
            if (i == SGO) {
                bar_sync(BAR_SGO, N_SGO);
                const int role = misc[34], col = warp * 16 + g + (t >> 1) * 8;
                const uint32_t fside = (role >> 6) * 64 + (col >> 2) * 2 + ((role >> 5) & 1) >= (int)misc[35];
                const int o = slot_off(role) + col * 4 + (t & 1) * 2;
                pubf = prm.arena + pick(AR_F + o, fside);
                pubs = prm.arena + pick(AR_S + o, fside);
                has_w2 = (role & 31) < 28;
            }
            if (i == CLRO) { st1(pd, 0u); st1(pd + 128, 0u); st1(pd + 1024, 0u); st1(pd + 1152, 0u); }
            if (i == CLRF && has_w2) st2(pubf, 0u, 0u);
            if (i == CLRS) st2(pubs, 0u, 0u);
            uint32_t a[16], b[8];
            ldsm4(ba, b); ldsm4(ba + 64, b + 4);
            ring.wait();
            const uint32_t aa = a_off + ring.slot * TILE_B;
#pragma unroll
            for (int k = 0; k < 4; k++) ldsm4t(aa + k * 2048, a + 4 * k);
            mma16816(c0, a[0], a[1], a[2], a[3], b[0], b[1]);
            mma16816(c1, a[4], a[5], a[6], a[7], b[2], b[3]);
            mma16816(c0, a[8], a[9], a[10], a[11], b[4], b[5]);
            mma16816(c1, a[12], a[13], a[14], a[15], b[6], b[7]);
            ring.release(lane);
            ba += 128;
        }
        if (sg == 1) {
#pragma unroll
            for (int k = 0; k < 4; k++) { vs[k] = c0[k]; vs[4 + k] = c1[k]; }
            continue;
        }
        const uint32_t r0 = tagged(hi ? c0[2] + c1[2] : c0[0] + c1[0], tag), r1 = tagged(hi ? c0[3] + c1[3] : c0[1] + c1[1], tag);
        if (sg == 4) st2(pubf, r0, r1);
        else {
            st1(pd, r0); st1(pd + 128, r1);
            if (sg == 3) { st1(pd + 1024, r0); st1(pd + 1152, r1); }
            if (sg != 2) bar_arrive(sg ? BAR_VGO : BAR_QGO, 384);
        }
    }
    bar_arrive(BAR_FGO, 288);
    {
        uint32_t a[8], b[16];
        float c[4][4];
#pragma unroll
        for (int k = 0; k < 4; k++) { c[k][0] = 0.f; c[k][1] = 0.f; c[k][2] = 0.f; c[k][3] = 0.f; }
        const uint32_t ap_off = sbase + (warp >> 2) * 4096 + a_lane;
        bar_sync(BAR_O, 384);
#pragma unroll
        for (int k = 0; k < 4; k++) ldsm4(b_off + SEG_O + k * 64, b + 4 * k);
#pragma unroll
        for (int q = 0; q < 4; q++) {
            const uint32_t bq = (q & 1) ? bar_half + (q >> 1) * 8 : ring.full + ring.slot * 8;
            const uint32_t pq = (q & 1) ? 0u : ring.phase;
            const uint32_t aa = ap_off + ring.slot * TILE_B + (q & 1) * (TILE_B / 2);
            if (q >= 2) mbar_spin(bq, pq); else mbar_wait(bq, pq);
            ldsm4t(aa, a); ldsm4t(aa + 2048, a + 4);
            mma16816(c[(2 * q) & 3], a[0], a[1], a[2], a[3], b[4 * q], b[4 * q + 1]);
            mma16816(c[(2 * q + 1) & 3], a[4], a[5], a[6], a[7], b[4 * q + 2], b[4 * q + 3]);
            if (q & 1) ring.next();
        }
        const float r0 = ((hi ? c[0][2] : c[0][0]) + (hi ? c[1][2] : c[1][0])) + ((hi ? c[2][2] : c[2][0]) + (hi ? c[3][2] : c[3][0]));
        const float r1 = ((hi ? c[0][3] : c[0][1]) + (hi ? c[1][3] : c[1][1])) + ((hi ? c[2][3] : c[2][1]) + (hi ? c[3][3] : c[3][1]));
        const uint32_t u0 = tagged(r0, tag), u1 = tagged(r1, tag);
        st2(pubs, u0, u1);
        bar_arrive(BAR_SREL, N_SREL);
        st2(reinterpret_cast<float*>(reinterpret_cast<uintptr_t>(pubs) ^ 4096u), 0u, 0u);
        if (has_w2) st2(reinterpret_cast<float*>(reinterpret_cast<uintptr_t>(pubf) ^ 4096u), 0u, 0u);
    }
}

typedef CUresult (*EncodeFn)(CUtensorMap*, CUtensorMapDataType, cuuint32_t, void*, const cuuint64_t*, const cuuint64_t*,
                             const cuuint32_t*, const cuuint32_t*, CUtensorMapInterleave, CUtensorMapSwizzle,
                             CUtensorMapL2promotion, CUtensorMapFloatOOBfill);

void make_map(EncodeFn enc, CUtensorMap* m, const void* base, uint64_t rows, uint64_t cols, uint32_t box_rows) {
    cuuint64_t dims[3] = {64, rows, cols / 64};
    cuuint64_t strides[2] = {cols * 2, 128};
    cuuint32_t box[3] = {64, box_rows, 2};
    cuuint32_t es[3] = {1, 1, 1};
    enc(m, CU_TENSOR_MAP_DATA_TYPE_BFLOAT16, 3, const_cast<void*>(base), dims, strides, box, es,
        CU_TENSOR_MAP_INTERLEAVE_NONE, CU_TENSOR_MAP_SWIZZLE_128B, CU_TENSOR_MAP_L2_PROMOTION_L2_256B,
        CU_TENSOR_MAP_FLOAT_OOB_FILL_NONE);
}

}

extern "C" void kernel_launch(void* const* d_in, const int* in_sizes, int n_in, void* d_out, int out_size) {
    (void)in_sizes; (void)n_in; (void)out_size;
    static EncodeFn enc = nullptr;
    static void* arena_ptr = nullptr;
    if (!enc) {
        void* fn = nullptr;
        cudaDriverEntryPointQueryResult qr;
        cudaGetDriverEntryPoint("cuTensorMapEncodeTiled", &fn, cudaEnableDefault, &qr);
        enc = (EncodeFn)fn;
        cudaGetSymbolAddress(&arena_ptr, g_arena);
        cudaFuncSetAttribute(fused_decode_kernel, cudaFuncAttributeMaxDynamicSharedMemorySize, SM_TOTAL + 1024);
    }
    Params prm;
    make_map(enc, &prm.m[0], d_in[3], 512, 4096, 64);
    make_map(enc, &prm.m[1], d_in[6], 512, 1792, 64);
    make_map(enc, &prm.m[2], d_in[1], 4ull * 8 * 16384, 128, 64);
    make_map(enc, &prm.m[3], d_in[2], 4ull * 8 * 16384, 128, 64);
    make_map(enc, &prm.m[4], d_in[7], 1792, 512, 64);
    make_map(enc, &prm.m[5], d_in[4], 4096, 512, 32);
    prm.raw[0] = (const char*)d_in[2];
    prm.raw[1] = (const char*)d_in[7];
    prm.raw[2] = (const char*)d_in[4];
    prm.x = (const __nv_bfloat16*)d_in[0];
    prm.out = (__nv_bfloat16*)d_out;
    prm.arena = (float*)(((uintptr_t)arena_ptr + 0x1fffffull) & ~0x1fffffull);
    fused_decode_kernel<<<NCTA, NTHREADS, SM_TOTAL + 1024>>>(prm);
}
```

```cpp
#include <cuda_runtime.h>
#include <cuda_bf16.h>
#include <cuda.h>
#include <stdint.h>

namespace {

constexpr int NCTA     = 128;
constexpr int NFFN     = 112;
constexpr int NSLOT    = 13;
constexpr int TILE_B   = 16384;
constexpr int KT       = 16;
constexpr int NS       = 3;
constexpr int NTHREADS = 448 + 32 * NS;

constexpr int TAU      = 657;
constexpr int LEAD     = 22;
constexpr int INFLIGHT = 8;
constexpr int TAILCAP  = 3;
constexpr int W1POS    = 6;
constexpr int QSLOT = 5;
constexpr int RGO   = 4;
constexpr int SGO   = 10;
constexpr int CLRO = 12, CLRF = 13, CLRS = 14;
constexpr unsigned SSTAG = 125;

constexpr int SEG_XN = 0;
constexpr int SEG_P  = 1024;
constexpr int SEG_H  = 3072;
constexpr int SEG_O  = 3200;
constexpr int SEG_Q  = 3456;
constexpr int ACT_PITCH = 3712 + 16;
constexpr int SM_ACT   = NSLOT * TILE_B;
constexpr int SM_WMAX  = SM_ACT + 4 * ACT_PITCH;
constexpr int SM_LSUM  = SM_WMAX + 128;
constexpr int SM_MISC  = SM_LSUM + 32;
constexpr int SM_BAR   = SM_MISC + 256;
constexpr int SM_TOTAL = SM_BAR + (2 * NSLOT + 2) * 8;
static_assert(SM_TOTAL + 1024 <= 232448, "smem");

constexpr int BAR_MMA = 1, BAR_XN = 2, BAR_Q = 3, BAR_H = 4, BAR_O = 5, BAR_VGO = 6, BAR_QGO = 7, BAR_SGO = 8,
              BAR_FGO = 9, BAR_SREL = 10, BAR_RGO = 11;
constexpr int N_SGO = 416 + 32 * NS, N_SREL = 256 + 32 * NS;

__device__ __align__(4096) float g_arena[1 << 20];
constexpr int AR_O = 0, AR_F = 131072, AR_S = 262144, AR_Q = 393216, AR_H = 458752;
constexpr int AR_XS = AR_F + 62 * 2048;
constexpr int AR_EPOCH = AR_XS + 2048;
constexpr uint32_t HOME_MASK = (1u << 12) | (1u << 13) | (1u << 16) | (1u << 17) | (1u << 19);

struct Params {
    CUtensorMap m[6];
    const char* raw[3];
    const __nv_bfloat16* x;
    __nv_bfloat16* out;
    float* arena;
};

constexpr unsigned SPIN_LIMIT = 1u << 20;

__device__ __forceinline__ int phase_key(int cta) { return (((cta >> 2) * 13) & 31) * 4 + (cta & 3); }
__device__ __forceinline__ int slot_off(int producer) { return (producer >> 1) * 2048 + (producer & 1) * 512; }
__device__ __forceinline__ uint32_t parity(int off) { return __popc(((uint32_t)off << 2) & HOME_MASK) & 1u; }
__device__ __forceinline__ int pick(int off, uint32_t side) { return off + (int)((parity(off) ^ side) << 10); }

__device__ __forceinline__ void mbar_init(uint32_t bar, uint32_t cnt) {
    asm volatile("mbarrier.init.shared::cta.b64 [%0], %1;" :: "r"(bar), "r"(cnt) : "memory");
}
__device__ __forceinline__ void mbar_expect_tx(uint32_t bar, uint32_t bytes) {
    asm volatile("mbarrier.arrive.expect_tx.shared::cta.b64 _, [%0], %1;" :: "r"(bar), "r"(bytes) : "memory");
}
__device__ __forceinline__ void mbar_arrive(uint32_t bar) {
    asm volatile("mbarrier.arrive.shared::cta.b64 _, [%0];" :: "r"(bar) : "memory");
}
__device__ __forceinline__ bool mbar_test(uint32_t bar, uint32_t par) {
    uint32_t ok;
    asm volatile("{\n .reg .pred p;\n mbarrier.test_wait.parity.shared::cta.b64 p, [%1], %2;\n selp.u32 %0, 1, 0, p;\n}"
                 : "=r"(ok) : "r"(bar), "r"(par) : "memory");
    return ok;
}
__device__ __forceinline__ void mbar_wait(uint32_t bar, uint32_t par) {
    uint32_t ok, it = 0;
    while (true) {
        asm volatile("{\n .reg .pred p;\n mbarrier.try_wait.parity.shared::cta.b64 p, [%1], %2, %3;\n selp.u32 %0, 1, 0, p;\n}"
                     : "=r"(ok) : "r"(bar), "r"(par), "r"(10000) : "memory");
        if (ok) break;
        if (++it > SPIN_LIMIT) __trap();
    }
}
__device__ __forceinline__ void mbar_spin(uint32_t bar, uint32_t par) {
    uint32_t ok, it = 0;
    while (true) {
        asm volatile("{\n .reg .pred p;\n mbarrier.try_wait.parity.shared::cta.b64 p, [%1], %2;\n selp.u32 %0, 1, 0, p;\n}"
                     : "=r"(ok) : "r"(bar), "r"(par) : "memory");
        if (ok) break;
        if (++it > 16 * SPIN_LIMIT) __trap();
    }
}
__device__ __forceinline__ void tma_tile(uint32_t dst, const CUtensorMap* tm, int row, int half, uint32_t bar) {
    asm volatile("cp.async.bulk.tensor.3d.shared::cluster.global.mbarrier::complete_tx::bytes.L2::cache_hint [%0], [%1, {%3, %4, %5}], [%2], %6;"
                 :: "r"(dst), "l"(tm), "r"(bar), "r"(0), "r"(row), "r"(half), "l"(0x12F0000000000000ull) : "memory");
}
__device__ __forceinline__ void ldsm4(uint32_t addr, uint32_t* r) {
    asm volatile("ldmatrix.sync.aligned.m8n8.x4.shared.b16 {%0,%1,%2,%3}, [%4];"
                 : "=r"(r[0]), "=r"(r[1]), "=r"(r[2]), "=r"(r[3]) : "r"(addr) : "memory");
}
__device__ __forceinline__ void ldsm4t(uint32_t addr, uint32_t* r) {
    asm volatile("ldmatrix.sync.aligned.m8n8.x4.trans.shared.b16 {%0,%1,%2,%3}, [%4];"
                 : "=r"(r[0]), "=r"(r[1]), "=r"(r[2]), "=r"(r[3]) : "r"(addr) : "memory");
}
__device__ __forceinline__ void mma16816(float (&c)[4], uint32_t a0, uint32_t a1, uint32_t a2, uint32_t a3,
                                         uint32_t b0, uint32_t b1) {
    asm volatile("mma.sync.aligned.m16n8k16.row.col.f32.bf16.bf16.f32 {%0,%1,%2,%3}, {%4,%5,%6,%7}, {%8,%9}, {%0,%1,%2,%3};"
                 : "+f"(c[0]), "+f"(c[1]), "+f"(c[2]), "+f"(c[3])
                 : "r"(a0), "r"(a1), "r"(a2), "r"(a3), "r"(b0), "r"(b1));
}
__device__ __forceinline__ void bar_sync(int id, int n) { asm volatile("bar.sync %0, %1;" :: "r"(id), "r"(n) : "memory"); }
__device__ __forceinline__ void bar_arrive(int id, int n) { asm volatile("bar.arrive %0, %1;" :: "r"(id), "r"(n) : "memory"); }
__device__ __forceinline__ unsigned gtime32() { unsigned t; asm volatile("mov.u32 %0, %%globaltimer_lo;" : "=r"(t)); return t; }
__device__ __forceinline__ unsigned clock32() { unsigned t; asm volatile("mov.u32 %0, %%clock;" : "=r"(t)); return t; }
__device__ __forceinline__ void delay(unsigned clocks) { const unsigned c0 = clock32(); while (clock32() - c0 < clocks) {} }

__device__ __forceinline__ float bf16r(float v) {
    uint32_t d; asm("cvt.rn.bf16x2.f32 %0, %1, %2;" : "=r"(d) : "f"(v), "f"(0.f));
    return __uint_as_float(d);
}
__device__ __forceinline__ uint32_t pack_bf16(float lo, float hi) {
    uint32_t d; asm("cvt.rn.bf16x2.f32 %0, %1, %2;" : "=r"(d) : "f"(hi), "f"(lo));
    return d;
}
__device__ __forceinline__ float bf_lo(uint32_t u) { return __uint_as_float(u << 16); }
__device__ __forceinline__ float bf_hi(uint32_t u) { return __uint_as_float(u & 0xffff0000u); }
__device__ __forceinline__ float asf(uint32_t u) { return __uint_as_float(u); }

__device__ __forceinline__ uint32_t tagged(float v, uint32_t tag) { return (__float_as_uint(v) & ~3u) | tag; }
__device__ __forceinline__ void st1(float* p, uint32_t u) {
    asm volatile("st.relaxed.gpu.global.u32 [%0], %1;" :: "l"(p), "r"(u) : "memory");
}
__device__ __forceinline__ void st2(float* p, uint32_t u0, uint32_t u1) {
    asm volatile("st.relaxed.gpu.global.v2.u32 [%0], {%1, %2};" :: "l"(p), "r"(u0), "r"(u1) : "memory");
}
__device__ __forceinline__ uint4 ld4(const float* p) {
    uint4 v;
    asm volatile("ld.relaxed.gpu.global.v4.u32 {%0,%1,%2,%3}, [%4];" : "=r"(v.x), "=r"(v.y), "=r"(v.z), "=r"(v.w) : "l"(p) : "memory");
    return v;
}
__device__ __forceinline__ uint32_t badbits(const uint4& v, uint32_t tag) {
    uint32_t a, b;
    asm("lop3.b32 %0, %1, %2, %3, 0x7e;" : "=r"(a) : "r"(v.x), "r"(tag), "r"(v.y));
    asm("lop3.b32 %0, %1, %2, %3, 0x7e;" : "=r"(b) : "r"(v.z), "r"(tag), "r"(v.w));
    return a | b;
}
__device__ __forceinline__ void gather4(uint4 (&v)[4], const float* p0, const float* p1, const float* p2, const float* p3, uint32_t tag) {
    v[0] = ld4(p0); v[1] = ld4(p1); v[2] = ld4(p2); v[3] = ld4(p3);
    unsigned it = 0;
    while (true) {
        const uint32_t b0 = badbits(v[0], tag), b1 = badbits(v[1], tag), b2 = badbits(v[2], tag), b3 = badbits(v[3], tag);
        if (!__any_sync(0xffffffffu, ((b0 | b1) | (b2 | b3)) & 3u)) break;
        if (b0 & 3u) v[0] = ld4(p0);
        if (b1 & 3u) v[1] = ld4(p1);
        if (b2 & 3u) v[2] = ld4(p2);
        if (b3 & 3u) v[3] = ld4(p3);
        if (++it > SPIN_LIMIT) __trap();
    }
}
__device__ __forceinline__ float4 sum4(const uint4 (&v)[4]) {
    return make_float4((asf(v[0].x) + asf(v[1].x)) + (asf(v[2].x) + asf(v[3].x)), (asf(v[0].y) + asf(v[1].y)) + (asf(v[2].y) + asf(v[3].y)),
                       (asf(v[0].z) + asf(v[1].z)) + (asf(v[2].z) + asf(v[3].z)), (asf(v[0].w) + asf(v[1].w)) + (asf(v[2].w) + asf(v[3].w)));
}
__device__ __forceinline__ uint32_t near_side(volatile uint32_t* misc) {
    const uint32_t m0 = min(min(misc[40], misc[42]), min(misc[44], misc[46]));
    const uint32_t m1 = min(min(misc[41], misc[43]), min(misc[45], misc[47]));
    return m1 < m0;
}

struct Ring {
    uint32_t full, empty;
    int slot; uint32_t phase;
    __device__ __forceinline__ void wait() { mbar_wait(full + slot * 8, phase); }
    __device__ __forceinline__ void next() { if (++slot == NSLOT) { slot = 0; phase ^= 1; } }
    __device__ __forceinline__ void release(int lane) {
        __syncwarp();
        if (lane == 0) mbar_arrive(empty + slot * 8);
        next();
    }
};

__global__ void __launch_bounds__(NTHREADS, 1)
fused_decode_kernel(const __grid_constant__ Params prm) {
    extern __shared__ uint8_t smem_raw[];
    const uint32_t sbase = ((uint32_t)__cvta_generic_to_shared(smem_raw) + 1023u) & ~1023u;
    uint8_t* sgen = smem_raw + (sbase - (uint32_t)__cvta_generic_to_shared(smem_raw));
    const int cta = blockIdx.x;
    const int hkv = cta >> 4, rhi = (cta >> 2) & 3, rlo = cta & 3;
    const bool has_w1 = cta < NFFN;
    const uint32_t bar_full = sbase + SM_BAR, bar_empty = bar_full + NSLOT * 8, bar_half = bar_empty + NSLOT * 8;

    if (threadIdx.x - 1u < 31u) return;
    if (threadIdx.x == 0) {
        const unsigned t0 = gtime32();
        mbar_init(bar_full, 1);
        asm volatile("fence.mbarrier_init.release.cluster;" ::: "memory");
        mbar_expect_tx(bar_full, TILE_B);
        tma_tile(sbase, &prm.m[0], rhi * 128, (hkv * 4 + rlo) * 2, bar_full);
#pragma unroll
        for (int i = 1; i < 2 * NSLOT + 2; i++) mbar_init(bar_full + i * 8, (i < NSLOT || i >= 2 * NSLOT) ? 1 : 8);
        asm volatile("fence.mbarrier_init.release.cluster;" ::: "memory");
        volatile uint32_t* prole = reinterpret_cast<volatile uint32_t*>(sgen + SM_MISC) + 34;
        *prole = 0xffffffffu;
        asm volatile("barrier.arrive %0, %1;" :: "n"(BAR_XN), "n"(448) : "memory");
        const int kvrow = (rhi * 8 + hkv) * 16384 + 12288 + rlo * 64;
        const int toff = ((phase_key(cta) >> 2) * TAU) / 32 - (LEAD * TAU) / 16;
        constexpr int P_W1 = 18 + W1POS, P_W2 = 35, P_END = 38;
        int slot = 1; uint32_t eph = 1;
        int fslot = 0; uint32_t fph = 0;
        int landed = 0, issued = 1;
        uint32_t role = 0;
#pragma unroll 1
        for (int v = 1; v < P_END; v++) {
            if (v == 31) {
                unsigned it = 0;
                while ((role = *prole) == 0xffffffffu) { if (++it > 16 * SPIN_LIMIT) __trap(); }
            }
            const int rh = role & 31, rc = role >> 5;
            const bool has_w2 = rh < 28;
            int mi, row, half;
            if (v == 1)          { mi = 0; row = rhi * 128 + 64; half = (hkv * 4 + rlo) * 2; }
            else if (v == P_W1)  { mi = 1; row = ((cta >> 1) & 7) * 64; half = (hkv * 2 + (cta & 1)) * 2; }
            else if (v < P_W2)   { const int j = v - 2 - (v > P_W1); mi = 2 + (j >> 4); row = kvrow + (j & 15) * 256; half = 0; }
            else if (v == P_W2)  { mi = 4; row = rh * 64; half = rc * 2; }
            else                 { mi = 5; row = rh * 128 + (v - P_W2 - 1) * 64; half = rc * 2; }
            if (v < 6) asm volatile("prefetch.tensormap [%0];" :: "l"(&prm.m[v]) : "memory");
            if (v == 10) asm volatile("cp.async.bulk.prefetch.L2.global [%0], 128;" :: "l"(prm.raw[0] + (size_t)kvrow * 256) : "memory");
            if (v == 31) {
                if (has_w2) asm volatile("cp.async.bulk.prefetch.L2.global [%0], 128;" :: "l"(prm.raw[1] + rh * 65536 + rc * 256) : "memory");
                asm volatile("cp.async.bulk.prefetch.L2.global [%0], 128;" :: "l"(prm.raw[2] + rh * 131072 + rc * 256) : "memory");
            }
            if ((v == P_W1 && !has_w1) || (v == P_W2 && !has_w2)) continue;
            const int need = issued + 1 - (v >= P_W2 ? TAILCAP : INFLIGHT);
            while (landed < need) {
                mbar_wait(bar_full + fslot * 8, fph);
                if (++fslot == NSLOT) { fslot = 0; fph ^= 1; }
                landed++;
            }
            if (issued >= NSLOT) mbar_wait(bar_empty + slot * 8, eph);
            {
                const int due = (v - (!has_w2 && v > P_W2)) * TAU + toff;
                int s2 = slot - 2; uint32_t par = eph ^ 1;
                if (s2 < 0) { s2 += NSLOT; par ^= 1; }
                while ((int)(gtime32() - t0) < due) {
                    if (v > 4 && mbar_test(bar_full + s2 * 8, par)) break;
                }
            }
            const uint32_t dst = sbase + slot * TILE_B, bf = bar_full + slot * 8;
            if (v > P_W2) {
                const uint32_t bh = bar_half + (v - P_W2 - 1) * 8;
                mbar_expect_tx(bf, TILE_B / 2);
                tma_tile(dst, &prm.m[5], row, half, bf);
                mbar_expect_tx(bh, TILE_B / 2);
                tma_tile(dst + TILE_B / 2, &prm.m[5], row + 32, half, bh);
            } else {
                mbar_expect_tx(bf, TILE_B);
                tma_tile(dst, &prm.m[mi], row, half, bf);
            }
            if (++slot == NSLOT) { slot = 0; eph ^= 1; }
            issued++;
        }
    }
    int tix;
    asm volatile("mov.u32 %0, %%tid.x;" : "=r"(tix));
    if (tix == 0) return;
    const int lane = tix & 31;
    const int wix = __shfl_sync(0xffffffffu, tix >> 5, 0);
    volatile uint32_t* misc = reinterpret_cast<volatile uint32_t*>(sgen + SM_MISC);

    if (wix < 5) {
        const int gw = wix - 1;
        {
            const uint4* xr = reinterpret_cast<const uint4*>(prm.x + gw * 512);
            const uint4 u0 = __ldg(xr + lane), u1 = __ldg(xr + 32 + lane);
            const uint32_t w[8] = {u0.x, u0.y, u0.z, u0.w, u1.x, u1.y, u1.z, u1.w};
            float s = 0.f;
#pragma unroll
            for (int i = 0; i < 8; i++) s += bf_lo(w[i]) + bf_hi(w[i]);
#pragma unroll
            for (int o = 16; o; o >>= 1) s += __shfl_xor_sync(0xffffffffu, s, o);
            const float mean = s * (1.f / 512.f);
            float vs = 0.f;
#pragma unroll
            for (int i = 0; i < 8; i++) { const float d0 = bf_lo(w[i]) - mean, d1 = bf_hi(w[i]) - mean; vs += d0 * d0 + d1 * d1; }
#pragma unroll
            for (int o = 16; o; o >>= 1) vs += __shfl_xor_sync(0xffffffffu, vs, o);
            const float mb = bf16r(mean);
            const float den = bf16r(sqrtf(bf16r(bf16r(vs * (1.f / 512.f)) + 1e-5f)));
#pragma unroll 1
            for (int h = 0; h < 2; h++) {
                const uint4 u = h ? u1 : u0;
                const uint32_t uu[4] = {u.x, u.y, u.z, u.w};
                uint32_t r[4];
#pragma unroll
                for (int i = 0; i < 4; i++)
                    r[i] = pack_bf16(__fdiv_rn(bf16r(bf_lo(uu[i]) - mb), den), __fdiv_rn(bf16r(bf_hi(uu[i]) - mb), den));
                *reinterpret_cast<uint4*>(sgen + SM_ACT + gw * ACT_PITCH + SEG_XN + h * 512 + lane * 16) = make_uint4(r[0], r[1], r[2], r[3]);
            }
        }
        bar_arrive(BAR_XN, 448);
        float wv[4] = {1.f, 1.f, 1.f, 1.f};
        const float* pa = prm.arena + AR_Q + (hkv * 16 + gw * 4) * 512 + rhi * 128 + lane * 4;
        const float* pb = pa + 1024;
#pragma unroll 1
        for (int r = 0; r < 2; r++) {
            bar_sync(r ? BAR_VGO : BAR_QGO, 384);
            const uint32_t tag = misc[32];
            if (r == 0) mbar_wait(bar_full + QSLOT * 8, 0);
            {
                uint4 v[4];
                gather4(v, pa, pa + 512, pb, pb + 512, tag);
                const float o0 = fmaf(wv[0], asf(v[0].x), wv[1] * asf(v[1].x)) + fmaf(wv[2], asf(v[2].x), wv[3] * asf(v[3].x));
                const float o1 = fmaf(wv[0], asf(v[0].y), wv[1] * asf(v[1].y)) + fmaf(wv[2], asf(v[2].y), wv[3] * asf(v[3].y));
                const float o2 = fmaf(wv[0], asf(v[0].z), wv[1] * asf(v[1].z)) + fmaf(wv[2], asf(v[2].z), wv[3] * asf(v[3].z));
                const float o3 = fmaf(wv[0], asf(v[0].w), wv[1] * asf(v[1].w)) + fmaf(wv[2], asf(v[2].w), wv[3] * asf(v[3].w));
                *reinterpret_cast<uint2*>(sgen + SM_ACT + gw * ACT_PITCH + (r ? SEG_O : SEG_Q) + lane * 8) =
                    make_uint2(pack_bf16(o0, o1), pack_bf16(o2, o3));
                bar_arrive(r ? BAR_O : BAR_Q, 384);
            }
            if (r) break;
            bar_sync(BAR_SGO, N_SGO);
            const int rh = misc[34] & 31;
            {
                const uint32_t side = near_side(misc);
                const int o = AR_O + slot_off((rh >> 2) * 16 + gw * 4) + (rh & 3) * 128 + lane * 4;
                pa = prm.arena + pick(o, side);
                pb = prm.arena + pick(o + 2048, side);
            }
            if (rh < 28) {
                const int rg = rh;
                const float* ph = prm.arena + AR_H + ((rg >> 1) * 8 + (lane >> 4) * 4) * 512 + gw * 128 + (rg & 1) * 64 + (lane & 15) * 4;
                uint4 v[4];
                gather4(v, ph, ph + 512, ph + 1024, ph + 1536, tag);
                float4 h = sum4(v);
                h.x += __shfl_xor_sync(0xffffffffu, h.x, 16); h.y += __shfl_xor_sync(0xffffffffu, h.y, 16);
                h.z += __shfl_xor_sync(0xffffffffu, h.z, 16); h.w += __shfl_xor_sync(0xffffffffu, h.w, 16);
                if (lane < 16)
                    *reinterpret_cast<uint2*>(sgen + SM_ACT + gw * ACT_PITCH + SEG_H + lane * 8) =
                        make_uint2(pack_bf16(fmaxf(h.x, 0.f), fmaxf(h.y, 0.f)), pack_bf16(fmaxf(h.z, 0.f), fmaxf(h.w, 0.f)));
                bar_arrive(BAR_H, 384);
            }
            {
                const float* ps = prm.arena + AR_XS + ((rh >> 2) * 16 + gw * 4 + (lane & 3)) * 8 + (rh & 2) * 2;
                uint4 v = ld4(ps);
                unsigned it = 0;
                while (__any_sync(0xffffffffu, badbits(v, tag) & 3u)) { v = ld4(ps); if (++it > SPIN_LIMIT) __trap(); }
                const float m = bf_hi((rh & 1) ? v.z : v.x);
                const float l = asf((rh & 1) ? v.w : v.y);
                float M = fmaxf(m, __shfl_xor_sync(0xffffffffu, m, 1));
                M = fmaxf(M, __shfl_xor_sync(0xffffffffu, M, 2));
                const float e = __expf(m - M);
                float L = e * l;
                L += __shfl_xor_sync(0xffffffffu, L, 1);
                L += __shfl_xor_sync(0xffffffffu, L, 2);
                const float wgt = e / L;
#pragma unroll
                for (int i = 0; i < 4; i++) wv[i] = __shfl_sync(0xffffffffu, wgt, i);
            }
        }
        return;
    }

    if (wix < 6 + NS) {
        const bool is_s = wix >= 6;
        if (wix == 6) { misc[lane] = 0xffffffffu; misc[33] = 0u; }
        if (wix == 5) {
            if (lane == 0) {
                unsigned epoch;
                asm volatile("ld.relaxed.gpu.global.u32 %0, [%1];" : "=r"(epoch) : "l"(prm.arena + AR_EPOCH) : "memory");
                misc[32] = epoch + 1;
            }
            __syncwarp();
            bar_arrive(BAR_XN, 448);
            bar_sync(BAR_RGO, 288);
            const uint32_t tg = misc[32];
            const float* pw = prm.arena + AR_XS + lane * 8;
            uint4 sw[4];
            gather4(sw, pw, pw + 256, pw + 512, pw + 768, tg);
            uint32_t n1 = 0, below = 0;
#pragma unroll
            for (int i = 0; i < 4; i++) {
                const uint32_t ones = __ballot_sync(0xffffffffu, sw[i].x & 4u);
                n1 += __popc(ones);
                below += __popc(ones & __ballot_sync(0xffffffffu, phase_key(i * 32 + lane) < phase_key(cta)));
            }
            if (lane == 0) {
                const uint32_t rank = near_side(misc) ? NCTA - n1 + below : phase_key(cta) - below;
                misc[34] = ((rank >> 6) * 2 + (rank & 1)) * 32 + ((rank & 63) >> 1);
            }
        }
        bar_sync(BAR_SGO, N_SGO);
        const uint32_t tag = misc[32];
        const int role = misc[34];
        const uint32_t side = role >> 6;
        const int p = lane >> 2;
        const int o = slot_off((role & ~31) + p) + (role & 31) * 16 + (lane & 3) * 4 + (is_s ? AR_S : AR_F);
        const float* s0 = prm.arena + pick(o, side);
        const float* s1 = prm.arena + pick(o + 8192, side);
        const float* s2 = prm.arena + pick(o + 16384, side);
        const float* s3 = prm.arena + pick(o + 24576, side);
        const bool u16 = lane & 16, u8 = lane & 8;
        uint4 v[4];
        if (!is_s) {
            const bool skip3 = p >= 4;
            if (skip3) s3 = s0;
            bar_sync(BAR_FGO, 288);
            gather4(v, s0, s1, s2, s3, tag);
            if (skip3) v[3] = make_uint4(0u, 0u, 0u, 0u);
            const float4 a = sum4(v);
            const float e0 = (u16 ? a.z : a.x) + __shfl_xor_sync(0xffffffffu, u16 ? a.x : a.z, 16);
            const float e1 = (u16 ? a.w : a.y) + __shfl_xor_sync(0xffffffffu, u16 ? a.y : a.w, 16);
            float c = (u8 ? e1 : e0) + __shfl_xor_sync(0xffffffffu, u8 ? e0 : e1, 8);
            c += __shfl_xor_sync(0xffffffffu, c, 4);
            const float f = bf16r(c);
            misc[lane] = __float_as_uint(bf16r(__fdividef(f, 1.f + __expf(-f))));
        } else {
            const int oidx = (lane >> 3) * 512 + role * 4 + (lane & 3);
            const float xfin = __bfloat162float(prm.x[oidx]);
            const unsigned long long optr = __shfl_sync(0xffffffffu, (unsigned long long)(prm.out + oidx), lane);
            const uint32_t zero = tag >> 8;
            const uint32_t gaddr = sbase + SM_MISC + lane * 4;
            const bool bump = (cta | lane | zero) == 0;
            bar_sync(BAR_SREL, N_SREL);
            if (wix > 6) delay((wix - 6) * SSTAG);
            unsigned it = 0;
            uint32_t gate, done, b0 = 1, b1 = 1, b2 = 1, b3 = 1;
            float k0, k1, t0, t1;
            while (true) {
                if (b0 & 3u) v[0] = ld4(s0);
                if (b1 & 3u) v[1] = ld4(s1);
                if (b2 & 3u) v[2] = ld4(s2);
                if (b3 & 3u) v[3] = ld4(s3);
                b0 = badbits(v[0], tag); b1 = badbits(v[1], tag); b2 = badbits(v[2], tag); b3 = badbits(v[3], tag);
                const uint32_t bad = (b0 | b1) | (b2 | b3);
                asm volatile("ld.volatile.shared.u32 %0, [%1];" : "=r"(done) : "r"(sbase + SM_MISC + 33 * 4 + (bad & zero)) : "memory");
                asm volatile("ld.volatile.shared.u32 %0, [%1];" : "=r"(gate) : "r"(gaddr + (bad & zero)) : "memory");
                const float4 a = sum4(v);
                k0 = u16 ? a.z : a.x; k1 = u16 ? a.w : a.y;
                t0 = __shfl_xor_sync(0xffffffffu, u16 ? a.x : a.z, 16);
                t1 = __shfl_xor_sync(0xffffffffu, u16 ? a.y : a.w, 16);
                const bool again = __any_sync(0xffffffffu, bad & 3u);
                asm volatile("{\n .reg .pred p;\n setp.eq.u32 p, %1, 0;\n @p st.volatile.shared.u32 [%0], %2;\n}"
                             :: "r"(sbase + SM_MISC + 33 * 4), "r"((uint32_t)again), "r"(tag) : "memory");
                if (!again) break;
                if (done) return;
                if (++it > SPIN_LIMIT) __trap();
            }
            const float e0 = k0 + t0, e1 = k1 + t1;
            float c = (u8 ? e1 : e0) + __shfl_xor_sync(0xffffffffu, u8 ? e0 : e1, 8);
            if (done) return;
            c += __shfl_xor_sync(0xffffffffu, c, 4);
            it = 0;
            while (gate == 0xffffffffu) { gate = misc[lane]; if (++it > 16 * SPIN_LIMIT) __trap(); }
            const float res = xfin + bf16r(bf16r(c) * asf(gate));
            asm volatile("st.global.u16 [%0], %1;" :: "l"(optr), "h"((unsigned short)pack_bf16(res, 0.f)) : "memory");
            if (bump) *reinterpret_cast<unsigned*>(prm.arena + AR_EPOCH) = (tag == 3) ? 0u : tag;
        }
        return;
    }

    const int warp = wix - (6 + NS);
    const int qslot = hkv * 16 + rlo * 4 + rhi, hslot = (hkv * 2 + (cta & 1)) * 8 + ((cta >> 1) & 7);
    {
        float* pr = prm.arena + pick(AR_O + slot_off(cta) + (warp >> 1) * 128, warp & 1);
        if (lane < 4) st2(pr + lane * 2, 0u, 0u);
        bar_sync(BAR_MMA, 256);
        delay(300);
        if (lane == 0) {
            uint32_t v, c1;
            const uint32_t c0 = clock32();
            asm volatile("atom.relaxed.gpu.global.add.u32 %0, [%1], 4;" : "=r"(v) : "l"(pr) : "memory");
            asm volatile("{\n .reg .pred p;\n setp.ne.u32 p, %1, 1;\n mov.u32 %0, 0;\n @p mov.u32 %0, %%clock;\n}" : "=r"(c1) : "r"(v));
            misc[40 + warp] = c1 - c0;
        }
        __syncwarp();
    }
    const int g = lane >> 2, t = lane & 3;
    Ring ring{bar_full, bar_empty, 0, 0u};
    const int lrow = lane & 7, lmat = lane >> 3;
    const uint32_t a_lane = (lrow + ((lmat >> 1) << 3)) * 128 + ((((warp & 3) * 2 + (lmat & 1)) ^ lrow) << 4);
    const uint32_t a_off = sbase + (warp >> 2) * 8192 + a_lane;
    const uint32_t b_off = sbase + SM_ACT + (lane & 3) * ACT_PITCH + lmat * 16;
    const bool hi = t >= 2;
    const int pofs = (t & 1) * 256 + warp * 16 + g + (t >> 1) * 8;
    float* const myslot = prm.arena + slot_off(cta);
    float* pubf = nullptr; float* pubs = nullptr;
    bool has_w2 = false;
    bar_sync(BAR_XN, 448);
    const uint32_t tag = misc[32];

    float vs[8] = {0.f, 0.f, 0.f, 0.f, 0.f, 0.f, 0.f, 0.f};
#pragma unroll 1
    for (int sg = 0; sg < 5; sg++) {
        if (sg == 1) {
            if (warp == 0 && lane < 4) st2(prm.arena + AR_XS + cta * 8 + lane * 2, 0u, 0u);
            bar_sync(BAR_Q, 384);
            uint32_t qa[16];
            const uint8_t* qs = sgen + SM_ACT + (g & 3) * ACT_PITCH + SEG_Q + t * 4;
#pragma unroll
            for (int k = 0; k < 16; k++) qa[k] = *reinterpret_cast<const uint32_t*>(qs + k * 16);
            const uint32_t k_off = sbase + (warp * 8 + lrow) * 128;
            const uint32_t sw0 = (lmat ^ lrow) << 4, sw1 = ((lmat + 4) ^ lrow) << 4;
            float mx = -INFINITY;
            uint8_t* sdst = sgen + SM_ACT + g * ACT_PITCH + SEG_P + (warp * 8 + 2 * t) * 2;
#pragma unroll 1
            for (int it = 0; it < KT; it++) {
                ring.wait();
                const uint32_t tb = ring.slot * TILE_B + k_off;
                uint32_t b[16];
                ldsm4(tb + sw0, b); ldsm4(tb + sw1, b + 4); ldsm4(tb + 8192 + sw0, b + 8); ldsm4(tb + 8192 + sw1, b + 12);
                float c0[4] = {0.f, 0.f, 0.f, 0.f}, c1[4] = {0.f, 0.f, 0.f, 0.f};
#pragma unroll
                for (int k = 0; k < 8; k += 2) {
                    mma16816(c0, qa[2 * k], 0u, qa[2 * k + 1], 0u, b[2 * k], b[2 * k + 1]);
                    mma16816(c1, qa[2 * k + 2], 0u, qa[2 * k + 3], 0u, b[2 * k + 2], b[2 * k + 3]);
                }
                ring.release(lane);
                const float scale = 0.08838834764831845f;
                const uint32_t sp = pack_bf16(bf16r(c0[0] + c1[0]) * scale, bf16r(c0[1] + c1[1]) * scale);
                mx = fmaxf(mx, fmaxf(bf_lo(sp), bf_hi(sp)));
                if (lane < 16) *reinterpret_cast<uint32_t*>(sdst + it * 128) = sp;
            }
            mx = fmaxf(mx, __shfl_xor_sync(0xffffffffu, mx, 1));
            mx = fmaxf(mx, __shfl_xor_sync(0xffffffffu, mx, 2));
            if (lane < 16 && t == 0) reinterpret_cast<float*>(sgen + SM_WMAX)[warp * 4 + g] = mx;
            bar_sync(BAR_MMA, 256);
            const int head = warp >> 1;
            const float* wm = reinterpret_cast<const float*>(sgen + SM_WMAX) + head;
            float m = wm[0];
#pragma unroll
            for (int i = 1; i < 8; i++) m = fmaxf(m, wm[4 * i]);
            uint8_t* pp = sgen + SM_ACT + head * ACT_PITCH + SEG_P + (warp & 1) * 1024 + lane * 16;
            float l = 0.f;
#pragma unroll 1
            for (int h = 0; h < 2; h++) {
                const uint4 u = *reinterpret_cast<const uint4*>(pp + h * 512);
                uint32_t w[4] = {u.x, u.y, u.z, u.w};
#pragma unroll
                for (int i = 0; i < 4; i++) {
                    const float L2E = 1.4426950408889634f;
                    const float p0 = exp2f((bf_lo(w[i]) - m) * L2E), p1 = exp2f((bf_hi(w[i]) - m) * L2E);
                    l += p0 + p1;
                    w[i] = pack_bf16(p0, p1);
                }
                *reinterpret_cast<uint4*>(pp + h * 512) = make_uint4(w[0], w[1], w[2], w[3]);
            }
#pragma unroll
            for (int o = 16; o; o >>= 1) l += __shfl_xor_sync(0xffffffffu, l, o);
            if (lane == 0) reinterpret_cast<float*>(sgen + SM_LSUM)[warp] = l;
            bar_sync(BAR_MMA, 256);
            if ((warp & 1) && lane < 2) {
                const float* ls = reinterpret_cast<const float*>(sgen + SM_LSUM);
                st1(prm.arena + AR_XS + cta * 8 + head * 2 + lane, lane ? tagged(ls[warp - 1] + ls[warp], tag) : (__float_as_uint(m) | tag | (near_side(misc) << 2)));
            }
        }
        if ((sg == 2 && !has_w1) || (sg == 4 && !has_w2)) continue;
        const int i0 = (sg == 3) ? W1POS : (sg == 1) ? 0 : 32;
        const int i1 = (sg == 3) ? KT : (sg == 1) ? W1POS : (sg == 0) ? 34 : 33;
        const int seg = (sg == 0) ? SEG_XN + rhi * 256 : (sg == 2) ? SEG_XN + ((cta >> 1) & 7) * 128 : (sg == 4) ? SEG_H : SEG_P + i0 * 128;
        float* const pd = (sg == 0 ? prm.arena + AR_Q + qslot * 512 : sg == 2 ? prm.arena + AR_H + hslot * 512 : myslot + AR_O) + pofs;
        uint32_t ba = b_off + seg;
        float c0[4], c1[4];
#pragma unroll
        for (int k = 0; k < 4; k++) { c0[k] = sg == 3 ? vs[k] : 0.f; c1[k] = sg == 3 ? vs[4 + k] : 0.f; }
        if (sg == 4) bar_sync(BAR_H, 384);
#pragma unroll 1
        for (int i = i0; i < i1; i++) {
            if (i == RGO) bar_arrive(BAR_RGO, 288);
            if (i == SGO) {
                bar_sync(BAR_SGO, N_SGO);
                const int role = misc[34], col = warp * 16 + g + (t >> 1) * 8;
                const int o = slot_off(role) + col * 4 + (t & 1) * 2;
                pubf = prm.arena + pick(AR_F + o, role >> 6);
                pubs = prm.arena + pick(AR_S + o, role >> 6);
                has_w2 = (role & 31) < 28;
            }
            if (i == CLRO) { st1(pd, 0u); st1(pd + 128, 0u); st1(pd + 1024, 0u); st1(pd + 1152, 0u); }
            if (i == CLRF && has_w2) st2(pubf, 0u, 0u);
            if (i == CLRS) st2(pubs, 0u, 0u);
            uint32_t a[16], b[8];
            ldsm4(ba, b); ldsm4(ba + 64, b + 4);
            ring.wait();
            const uint32_t aa = a_off + ring.slot * TILE_B;
#pragma unroll
            for (int k = 0; k < 4; k++) ldsm4t(aa + k * 2048, a + 4 * k);
            mma16816(c0, a[0], a[1], a[2], a[3], b[0], b[1]);
            mma16816(c1, a[4], a[5], a[6], a[7], b[2], b[3]);
            mma16816(c0, a[8], a[9], a[10], a[11], b[4], b[5]);
            mma16816(c1, a[12], a[13], a[14], a[15], b[6], b[7]);
            ring.release(lane);
            ba += 128;
        }
        if (sg == 1) {
#pragma unroll
            for (int k = 0; k < 4; k++) { vs[k] = c0[k]; vs[4 + k] = c1[k]; }
            continue;
        }
        const uint32_t r0 = tagged(hi ? c0[2] + c1[2] : c0[0] + c1[0], tag), r1 = tagged(hi ? c0[3] + c1[3] : c0[1] + c1[1], tag);
        if (sg == 4) st2(pubf, r0, r1);
        else {
            st1(pd, r0); st1(pd + 128, r1);
            if (sg == 3) { st1(pd + 1024, r0); st1(pd + 1152, r1); }
            if (sg != 2) bar_arrive(sg ? BAR_VGO : BAR_QGO, 384);
        }
    }
    bar_arrive(BAR_FGO, 288);
    {
        uint32_t a[8], b[16];
        float c[4][4];
#pragma unroll
        for (int k = 0; k < 4; k++) { c[k][0] = 0.f; c[k][1] = 0.f; c[k][2] = 0.f; c[k][3] = 0.f; }
        const uint32_t ap_off = sbase + (warp >> 2) * 4096 + a_lane;
        bar_sync(BAR_O, 384);
#pragma unroll
        for (int k = 0; k < 4; k++) ldsm4(b_off + SEG_O + k * 64, b + 4 * k);
#pragma unroll
        for (int q = 0; q < 4; q++) {
            const uint32_t bq = (q & 1) ? bar_half + (q >> 1) * 8 : ring.full + ring.slot * 8;
            const uint32_t pq = (q & 1) ? 0u : ring.phase;
            const uint32_t aa = ap_off + ring.slot * TILE_B + (q & 1) * (TILE_B / 2);
            if (q >= 2) mbar_spin(bq, pq); else mbar_wait(bq, pq);
            ldsm4t(aa, a); ldsm4t(aa + 2048, a + 4);
            mma16816(c[(2 * q) & 3], a[0], a[1], a[2], a[3], b[4 * q], b[4 * q + 1]);
            mma16816(c[(2 * q + 1) & 3], a[4], a[5], a[6], a[7], b[4 * q + 2], b[4 * q + 3]);
            if (q & 1) ring.next();
        }
        const float r0 = ((hi ? c[0][2] : c[0][0]) + (hi ? c[1][2] : c[1][0])) + ((hi ? c[2][2] : c[2][0]) + (hi ? c[3][2] : c[3][0]));
        const float r1 = ((hi ? c[0][3] : c[0][1]) + (hi ? c[1][3] : c[1][1])) + ((hi ? c[2][3] : c[2][1]) + (hi ? c[3][3] : c[3][1]));
        const uint32_t u0 = tagged(r0, tag), u1 = tagged(r1, tag);
        st2(pubs, u0, u1);
        bar_arrive(BAR_SREL, N_SREL);
    }
}

typedef CUresult (*EncodeFn)(CUtensorMap*, CUtensorMapDataType, cuuint32_t, void*, const cuuint64_t*, const cuuint64_t*,
                             const cuuint32_t*, const cuuint32_t*, CUtensorMapInterleave, CUtensorMapSwizzle,
                             CUtensorMapL2promotion, CUtensorMapFloatOOBfill);

void make_map(EncodeFn enc, CUtensorMap* m, const void* base, uint64_t rows, uint64_t cols, uint32_t box_rows) {
    cuuint64_t dims[3] = {64, rows, cols / 64};
    cuuint64_t strides[2] = {cols * 2, 128};
    cuuint32_t box[3] = {64, box_rows, 2};
    cuuint32_t es[3] = {1, 1, 1};
    enc(m, CU_TENSOR_MAP_DATA_TYPE_BFLOAT16, 3, const_cast<void*>(base), dims, strides, box, es,
        CU_TENSOR_MAP_INTERLEAVE_NONE, CU_TENSOR_MAP_SWIZZLE_128B, CU_TENSOR_MAP_L2_PROMOTION_L2_256B,
        CU_TENSOR_MAP_FLOAT_OOB_FILL_NONE);
}

}

extern "C" void kernel_launch(void* const* d_in, const int* in_sizes, int n_in, void* d_out, int out_size) {
    (void)in_sizes; (void)n_in; (void)out_size;
    static EncodeFn enc = nullptr;
    static void* arena_ptr = nullptr;
    if (!enc) {
        void* fn = nullptr;
        cudaDriverEntryPointQueryResult qr;
        cudaGetDriverEntryPoint("cuTensorMapEncodeTiled", &fn, cudaEnableDefault, &qr);
        enc = (EncodeFn)fn;
        cudaGetSymbolAddress(&arena_ptr, g_arena);
        cudaFuncSetAttribute(fused_decode_kernel, cudaFuncAttributeMaxDynamicSharedMemorySize, SM_TOTAL + 1024);
    }
    Params prm;
    make_map(enc, &prm.m[0], d_in[3], 512, 4096, 64);
    make_map(enc, &prm.m[1], d_in[6], 512, 1792, 64);
    make_map(enc, &prm.m[2], d_in[1], 4ull * 8 * 16384, 128, 64);
    make_map(enc, &prm.m[3], d_in[2], 4ull * 8 * 16384, 128, 64);
    make_map(enc, &prm.m[4], d_in[7], 1792, 512, 64);
    make_map(enc, &prm.m[5], d_in[4], 4096, 512, 32);
    prm.raw[0] = (const char*)d_in[2];
    prm.raw[1] = (const char*)d_in[7];
    prm.raw[2] = (const char*)d_in[4];
    prm.x = (const __nv_bfloat16*)d_in[0];
    prm.out = (__nv_bfloat16*)d_out;
    prm.arena = (float*)(((uintptr_t)arena_ptr + 0x1fffffull) & ~0x1fffffull);
    fused_decode_kernel<<<NCTA, NTHREADS, SM_TOTAL + 1024>>>(prm);
}
```

```cpp
#include <cuda_runtime.h>
#include <cuda_bf16.h>
#include <cuda.h>
#include <stdint.h>

namespace {

constexpr int NCTA     = 128;
constexpr int NFFN     = 112;
constexpr int NSLOT    = 13;
constexpr int TILE_B   = 16384;
constexpr int KT       = 16;
constexpr int NS       = 3;
constexpr int NTHREADS = 448 + 32 * NS;

constexpr int TAU      = 657;
constexpr int LEAD     = 22;
constexpr int INFLIGHT = 8;
constexpr int TAILCAP  = 3;
constexpr int W1POS    = 6;
constexpr int QSLOT = 5;
constexpr int RGO   = 4;
constexpr int SGO   = 10;
constexpr int CLRO = 12, CLRF = 13, CLRS = 14;
constexpr unsigned SSTAG = 125;

constexpr int SEG_XN = 0;
constexpr int SEG_P  = 1024;
constexpr int SEG_H  = 3072;
constexpr int SEG_O  = 3200;
constexpr int SEG_Q  = 3456;
constexpr int ACT_PITCH = 3712 + 16;
constexpr int SM_ACT   = NSLOT * TILE_B;
constexpr int SM_WMAX  = SM_ACT + 4 * ACT_PITCH;
constexpr int SM_LSUM  = SM_WMAX + 128;
constexpr int SM_MISC  = SM_LSUM + 32;
constexpr int SM_BAR   = SM_MISC + 256;
constexpr int SM_TOTAL = SM_BAR + (2 * NSLOT + 2) * 8;
static_assert(SM_TOTAL + 1024 <= 232448, "smem");

constexpr int BAR_MMA = 1, BAR_XN = 2, BAR_Q = 3, BAR_H = 4, BAR_O = 5, BAR_VGO = 6, BAR_QGO = 7, BAR_SGO = 8,
              BAR_FGO = 9, BAR_SREL = 10, BAR_RGO = 11;
constexpr int N_SGO = 416 + 32 * NS, N_SREL = 256 + 32 * NS;

__device__ __align__(4096) float g_arena[1 << 20];
constexpr int AR_O = 0, AR_F = 131072, AR_S = 262144, AR_Q = 393216, AR_H = 458752;
constexpr int S_TO_F = AR_S - AR_F;
constexpr int AR_XS = AR_F + 62 * 2048;
constexpr int AR_EPOCH = AR_XS + 2048;
constexpr uint32_t HOME_MASK = (1u << 12) | (1u << 13) | (1u << 16) | (1u << 17) | (1u << 19);

struct Params {
    CUtensorMap m[6];
    const char* raw[3];
    const __nv_bfloat16* x;
    __nv_bfloat16* out;
    float* arena;
};

constexpr unsigned SPIN_LIMIT = 1u << 20;

__device__ __forceinline__ int phase_key(int cta) { return (((cta >> 2) * 13) & 31) * 4 + (cta & 3); }
__device__ __forceinline__ int slot_off(int producer) { return (producer >> 1) * 2048 + (producer & 1) * 512; }
__device__ __forceinline__ uint32_t parity(int off) { return __popc(((uint32_t)off << 2) & HOME_MASK) & 1u; }
__device__ __forceinline__ int pick(int off, uint32_t side) { return off + (int)((parity(off) ^ side) << 10); }

__device__ __forceinline__ void mbar_init(uint32_t bar, uint32_t cnt) {
    asm volatile("mbarrier.init.shared::cta.b64 [%0], %1;" :: "r"(bar), "r"(cnt) : "memory");
}
__device__ __forceinline__ void mbar_expect_tx(uint32_t bar, uint32_t bytes) {
    asm volatile("mbarrier.arrive.expect_tx.shared::cta.b64 _, [%0], %1;" :: "r"(bar), "r"(bytes) : "memory");
}
__device__ __forceinline__ void mbar_arrive(uint32_t bar) {
    asm volatile("mbarrier.arrive.shared::cta.b64 _, [%0];" :: "r"(bar) : "memory");
}
__device__ __forceinline__ bool mbar_test(uint32_t bar, uint32_t par) {
    uint32_t ok;
    asm volatile("{\n .reg .pred p;\n mbarrier.test_wait.parity.shared::cta.b64 p, [%1], %2;\n selp.u32 %0, 1, 0, p;\n}"
                 : "=r"(ok) : "r"(bar), "r"(par) : "memory");
    return ok;
}
__device__ __forceinline__ void mbar_wait(uint32_t bar, uint32_t par) {
    uint32_t ok, it = 0;
    while (true) {
        asm volatile("{\n .reg .pred p;\n mbarrier.try_wait.parity.shared::cta.b64 p, [%1], %2, %3;\n selp.u32 %0, 1, 0, p;\n}"
                     : "=r"(ok) : "r"(bar), "r"(par), "r"(10000) : "memory");
        if (ok) break;
        if (++it > SPIN_LIMIT) __trap();
    }
}
__device__ __forceinline__ void mbar_spin(uint32_t bar, uint32_t par) {
    uint32_t ok, it = 0;
    while (true) {
        asm volatile("{\n .reg .pred p;\n mbarrier.try_wait.parity.shared::cta.b64 p, [%1], %2;\n selp.u32 %0, 1, 0, p;\n}"
                     : "=r"(ok) : "r"(bar), "r"(par) : "memory");
        if (ok) break;
        if (++it > 16 * SPIN_LIMIT) __trap();
    }
}
__device__ __forceinline__ void tma_tile(uint32_t dst, const CUtensorMap* tm, int row, int half, uint32_t bar) {
    asm volatile("cp.async.bulk.tensor.3d.shared::cluster.global.mbarrier::complete_tx::bytes.L2::cache_hint [%0], [%1, {%3, %4, %5}], [%2], %6;"
                 :: "r"(dst), "l"(tm), "r"(bar), "r"(0), "r"(row), "r"(half), "l"(0x12F0000000000000ull) : "memory");
}
__device__ __forceinline__ void ldsm4(uint32_t addr, uint32_t* r) {
    asm volatile("ldmatrix.sync.aligned.m8n8.x4.shared.b16 {%0,%1,%2,%3}, [%4];"
                 : "=r"(r[0]), "=r"(r[1]), "=r"(r[2]), "=r"(r[3]) : "r"(addr) : "memory");
}
__device__ __forceinline__ void ldsm4t(uint32_t addr, uint32_t* r) {
    asm volatile("ldmatrix.sync.aligned.m8n8.x4.trans.shared.b16 {%0,%1,%2,%3}, [%4];"
                 : "=r"(r[0]), "=r"(r[1]), "=r"(r[2]), "=r"(r[3]) : "r"(addr) : "memory");
}
__device__ __forceinline__ void mma16816(float (&c)[4], uint32_t a0, uint32_t a1, uint32_t a2, uint32_t a3,
                                         uint32_t b0, uint32_t b1) {
    asm volatile("mma.sync.aligned.m16n8k16.row.col.f32.bf16.bf16.f32 {%0,%1,%2,%3}, {%4,%5,%6,%7}, {%8,%9}, {%0,%1,%2,%3};"
                 : "+f"(c[0]), "+f"(c[1]), "+f"(c[2]), "+f"(c[3])
                 : "r"(a0), "r"(a1), "r"(a2), "r"(a3), "r"(b0), "r"(b1));
}
__device__ __forceinline__ void bar_sync(int id, int n) { asm volatile("bar.sync %0, %1;" :: "r"(id), "r"(n) : "memory"); }
__device__ __forceinline__ void bar_arrive(int id, int n) { asm volatile("bar.arrive %0, %1;" :: "r"(id), "r"(n) : "memory"); }
__device__ __forceinline__ unsigned gtime32() { unsigned t; asm volatile("mov.u32 %0, %%globaltimer_lo;" : "=r"(t)); return t; }
__device__ __forceinline__ unsigned clock32() { unsigned t; asm volatile("mov.u32 %0, %%clock;" : "=r"(t)); return t; }
__device__ __forceinline__ void delay(unsigned clocks) { const unsigned c0 = clock32(); while (clock32() - c0 < clocks) {} }

__device__ __forceinline__ float bf16r(float v) {
    uint32_t d; asm("cvt.rn.bf16x2.f32 %0, %1, %2;" : "=r"(d) : "f"(v), "f"(0.f));
    return __uint_as_float(d);
}
__device__ __forceinline__ uint32_t pack_bf16(float lo, float hi) {
    uint32_t d; asm("cvt.rn.bf16x2.f32 %0, %1, %2;" : "=r"(d) : "f"(hi), "f"(lo));
    return d;
}
__device__ __forceinline__ float bf_lo(uint32_t u) { return __uint_as_float(u << 16); }
__device__ __forceinline__ float bf_hi(uint32_t u) { return __uint_as_float(u & 0xffff0000u); }
__device__ __forceinline__ float ex2(float v) { float r; asm("ex2.approx.ftz.f32 %0, %1;" : "=f"(r) : "f"(v)); return r; }
__device__ __forceinline__ float asf(uint32_t u) { return __uint_as_float(u); }

__device__ __forceinline__ uint32_t tagged(float v, uint32_t tag) { return (__float_as_uint(v) & ~3u) | tag; }
__device__ __forceinline__ void st1(float* p, uint32_t u) {
    asm volatile("st.relaxed.gpu.global.u32 [%0], %1;" :: "l"(p), "r"(u) : "memory");
}
__device__ __forceinline__ void st2(float* p, uint32_t u0, uint32_t u1) {
    asm volatile("st.relaxed.gpu.global.v2.u32 [%0], {%1, %2};" :: "l"(p), "r"(u0), "r"(u1) : "memory");
}
__device__ __forceinline__ void st2_if(bool c, float* p, uint32_t u0, uint32_t u1) {
    asm volatile("{\n .reg .pred p;\n setp.ne.u32 p, %3, 0;\n @p st.relaxed.gpu.global.v2.u32 [%0], {%1, %2};\n}"
                 :: "l"(p), "r"(u0), "r"(u1), "r"((uint32_t)c) : "memory");
}
__device__ __forceinline__ void clear4(const float* p) {
    asm volatile("st.relaxed.gpu.global.v4.u32 [%0], {%1,%1,%1,%1};" :: "l"(p), "r"(0u) : "memory");
}
__device__ __forceinline__ float* other(float* p) { return reinterpret_cast<float*>(reinterpret_cast<uintptr_t>(p) ^ 4096u); }
__device__ __forceinline__ uint4 ld4(const float* p) {
    uint4 v;
    asm volatile("ld.relaxed.gpu.global.v4.u32 {%0,%1,%2,%3}, [%4];" : "=r"(v.x), "=r"(v.y), "=r"(v.z), "=r"(v.w) : "l"(p) : "memory");
    return v;
}
__device__ __forceinline__ uint32_t badbits(const uint4& v, uint32_t tag) {
    uint32_t a, b;
    asm("lop3.b32 %0, %1, %2, %3, 0x7e;" : "=r"(a) : "r"(v.x), "r"(tag), "r"(v.y));
    asm("lop3.b32 %0, %1, %2, %3, 0x7e;" : "=r"(b) : "r"(v.z), "r"(tag), "r"(v.w));
    return a | b;
}
__device__ __forceinline__ void gather4(uint4 (&v)[4], const float* p0, const float* p1, const float* p2, const float* p3, uint32_t tag) {
    v[0] = ld4(p0); v[1] = ld4(p1); v[2] = ld4(p2); v[3] = ld4(p3);
    unsigned it = 0;
    while (true) {
        const uint32_t b0 = badbits(v[0], tag), b1 = badbits(v[1], tag), b2 = badbits(v[2], tag), b3 = badbits(v[3], tag);
        if (!__any_sync(0xffffffffu, ((b0 | b1) | (b2 | b3)) & 3u)) break;
        if (b0 & 3u) v[0] = ld4(p0);
        if (b1 & 3u) v[1] = ld4(p1);
        if (b2 & 3u) v[2] = ld4(p2);
        if (b3 & 3u) v[3] = ld4(p3);
        if (++it > SPIN_LIMIT) __trap();
    }
}
__device__ __forceinline__ float4 sum4(const uint4 (&v)[4]) {
    return make_float4((asf(v[0].x) + asf(v[1].x)) + (asf(v[2].x) + asf(v[3].x)), (asf(v[0].y) + asf(v[1].y)) + (asf(v[2].y) + asf(v[3].y)),
                       (asf(v[0].z) + asf(v[1].z)) + (asf(v[2].z) + asf(v[3].z)), (asf(v[0].w) + asf(v[1].w)) + (asf(v[2].w) + asf(v[3].w)));
}
__device__ __forceinline__ uint32_t near_side(volatile uint32_t* misc) {
    const uint32_t m0 = min(min(misc[40], misc[42]), min(misc[44], misc[46]));
    const uint32_t m1 = min(min(misc[41], misc[43]), min(misc[45], misc[47]));
    return m1 < m0;
}

struct Ring {
    uint32_t full, empty;
    int slot; uint32_t phase;
    __device__ __forceinline__ void wait() { mbar_wait(full + slot * 8, phase); }
    __device__ __forceinline__ void next() { if (++slot == NSLOT) { slot = 0; phase ^= 1; } }
    __device__ __forceinline__ void release(int lane) {
        __syncwarp();
        if (lane == 0) mbar_arrive(empty + slot * 8);
        next();
    }
};

__global__ void __launch_bounds__(NTHREADS, 1)
fused_decode_kernel(const __grid_constant__ Params prm) {
    extern __shared__ uint8_t smem_raw[];
    const uint32_t sbase = ((uint32_t)__cvta_generic_to_shared(smem_raw) + 1023u) & ~1023u;
    uint8_t* sgen = smem_raw + (sbase - (uint32_t)__cvta_generic_to_shared(smem_raw));
    const int cta = blockIdx.x;
    const int hkv = cta >> 4, rhi = (cta >> 2) & 3, rlo = cta & 3;
    const bool has_w1 = cta < NFFN;
    const uint32_t bar_full = sbase + SM_BAR, bar_empty = bar_full + NSLOT * 8, bar_half = bar_empty + NSLOT * 8;

    if (threadIdx.x - 1u < 31u) return;
    if (threadIdx.x == 0) {
        const unsigned t0 = gtime32();
        mbar_init(bar_full, 1);
        asm volatile("fence.mbarrier_init.release.cluster;" ::: "memory");
        mbar_expect_tx(bar_full, TILE_B);
        tma_tile(sbase, &prm.m[0], rhi * 128, (hkv * 4 + rlo) * 2, bar_full);
#pragma unroll
        for (int i = 1; i < 2 * NSLOT + 2; i++) mbar_init(bar_full + i * 8, (i < NSLOT || i >= 2 * NSLOT) ? 1 : 8);
        asm volatile("fence.mbarrier_init.release.cluster;" ::: "memory");
        volatile uint32_t* prole = reinterpret_cast<volatile uint32_t*>(sgen + SM_MISC) + 34;
        *prole = 0xffffffffu;
        asm volatile("barrier.arrive %0, %1;" :: "n"(BAR_XN), "n"(448) : "memory");
        const int kvrow = (rhi * 8 + hkv) * 16384 + 12288 + rlo * 64;
        const int toff = ((phase_key(cta) >> 2) * TAU) / 32 - (LEAD * TAU) / 16;
        constexpr int P_W1 = 18 + W1POS, P_W2 = 35, P_END = 38;
        int slot = 1; uint32_t eph = 1;
        int fslot = 0; uint32_t fph = 0;
        int landed = 0, issued = 1;
        uint32_t role = 0;
#pragma unroll 1
        for (int v = 1; v < P_END; v++) {
            if (v == 31) {
                unsigned it = 0;
                while ((role = *prole) == 0xffffffffu) { if (++it > 16 * SPIN_LIMIT) __trap(); }
            }
            const int rh = role & 31, rc = role >> 5;
            const bool has_w2 = rh < 28;
            int mi, row, half;
            if (v == 1)          { mi = 0; row = rhi * 128 + 64; half = (hkv * 4 + rlo) * 2; }
            else if (v == P_W1)  { mi = 1; row = ((cta >> 1) & 7) * 64; half = (hkv * 2 + (cta & 1)) * 2; }
            else if (v < P_W2)   { const int j = v - 2 - (v > P_W1); mi = 2 + (j >> 4); row = kvrow + (j & 15) * 256; half = 0; }
            else if (v == P_W2)  { mi = 4; row = rh * 64; half = rc * 2; }
            else                 { mi = 5; row = rh * 128 + (v - P_W2 - 1) * 64; half = rc * 2; }
            if (v < 6) asm volatile("prefetch.tensormap [%0];" :: "l"(&prm.m[v]) : "memory");
            if (v == 10) asm volatile("cp.async.bulk.prefetch.L2.global [%0], 128;" :: "l"(prm.raw[0] + (size_t)kvrow * 256) : "memory");
            if (v == 31) {
                if (has_w2) asm volatile("cp.async.bulk.prefetch.L2.global [%0], 128;" :: "l"(prm.raw[1] + rh * 65536 + rc * 256) : "memory");
                asm volatile("cp.async.bulk.prefetch.L2.global [%0], 128;" :: "l"(prm.raw[2] + rh * 131072 + rc * 256) : "memory");
            }
            if ((v == P_W1 && !has_w1) || (v == P_W2 && !has_w2)) continue;
            const int need = issued + 1 - (v >= P_W2 ? TAILCAP : INFLIGHT);
            while (landed < need) {
                mbar_wait(bar_full + fslot * 8, fph);
                if (++fslot == NSLOT) { fslot = 0; fph ^= 1; }
                landed++;
            }
            if (issued >= NSLOT) mbar_wait(bar_empty + slot * 8, eph);
            {
                const int due = (v - (!has_w2 && v > P_W2)) * TAU + toff;
                int s2 = slot - 2; uint32_t par = eph ^ 1;
                if (s2 < 0) { s2 += NSLOT; par ^= 1; }
                while ((int)(gtime32() - t0) < due) {
                    if (v > 4 && mbar_test(bar_full + s2 * 8, par)) break;
                }
            }
            const uint32_t dst = sbase + slot * TILE_B, bf = bar_full + slot * 8;
            if (v > P_W2) {
                const uint32_t bh = bar_half + (v - P_W2 - 1) * 8;
                mbar_expect_tx(bf, TILE_B / 2);
                tma_tile(dst, &prm.m[5], row, half, bf);
                mbar_expect_tx(bh, TILE_B / 2);
                tma_tile(dst + TILE_B / 2, &prm.m[5], row + 32, half, bh);
            } else {
                mbar_expect_tx(bf, TILE_B);
                tma_tile(dst, &prm.m[mi], row, half, bf);
            }
            if (++slot == NSLOT) { slot = 0; eph ^= 1; }
            issued++;
        }
    }
    int tix;
    asm volatile("mov.u32 %0, %%tid.x;" : "=r"(tix));
    if (tix == 0) return;
    const int lane = tix & 31;
    const int wix = __shfl_sync(0xffffffffu, tix >> 5, 0);
    volatile uint32_t* misc = reinterpret_cast<volatile uint32_t*>(sgen + SM_MISC);

    if (wix < 5) {
        const int gw = wix - 1;
        {
            const uint4* xr = reinterpret_cast<const uint4*>(prm.x + gw * 512);
            const uint4 u0 = __ldg(xr + lane), u1 = __ldg(xr + 32 + lane);
            const uint32_t w[8] = {u0.x, u0.y, u0.z, u0.w, u1.x, u1.y, u1.z, u1.w};
            float s = 0.f;
#pragma unroll
            for (int i = 0; i < 8; i++) s += bf_lo(w[i]) + bf_hi(w[i]);
#pragma unroll
            for (int o = 16; o; o >>= 1) s += __shfl_xor_sync(0xffffffffu, s, o);
            const float mean = s * (1.f / 512.f);
            float vs = 0.f;
#pragma unroll
            for (int i = 0; i < 8; i++) { const float d0 = bf_lo(w[i]) - mean, d1 = bf_hi(w[i]) - mean; vs += d0 * d0 + d1 * d1; }
#pragma unroll
            for (int o = 16; o; o >>= 1) vs += __shfl_xor_sync(0xffffffffu, vs, o);
            const float mb = bf16r(mean);
            float den, rden;
            asm("sqrt.approx.f32 %0, %1;" : "=f"(den) : "f"(bf16r(bf16r(vs * (1.f / 512.f)) + 1e-5f)));
            asm("rcp.approx.f32 %0, %1;" : "=f"(rden) : "f"(bf16r(den)));
            uint32_t r[8];
#pragma unroll
            for (int i = 0; i < 8; i++) r[i] = pack_bf16(bf16r(bf_lo(w[i]) - mb) * rden, bf16r(bf_hi(w[i]) - mb) * rden);
            uint8_t* xs = sgen + SM_ACT + gw * ACT_PITCH + SEG_XN + lane * 16;
            *reinterpret_cast<uint4*>(xs) = make_uint4(r[0], r[1], r[2], r[3]);
            *reinterpret_cast<uint4*>(xs + 512) = make_uint4(r[4], r[5], r[6], r[7]);
        }
        bar_arrive(BAR_XN, 448);
        float wv[4] = {1.f, 1.f, 1.f, 1.f};
        const float* pa = prm.arena + AR_Q + (hkv * 16 + gw * 4) * 512 + rhi * 128 + lane * 4;
        const float* pb = pa + 1024;
#pragma unroll 1
        for (int r = 0; r < 2; r++) {
            bar_sync(r ? BAR_VGO : BAR_QGO, 384);
            const uint32_t tag = misc[32];
            if (r == 0) mbar_wait(bar_full + QSLOT * 8, 0);
            {
                uint4 v[4];
                gather4(v, pa, pa + 512, pb, pb + 512, tag);
                const float o0 = fmaf(wv[0], asf(v[0].x), wv[1] * asf(v[1].x)) + fmaf(wv[2], asf(v[2].x), wv[3] * asf(v[3].x));
                const float o1 = fmaf(wv[0], asf(v[0].y), wv[1] * asf(v[1].y)) + fmaf(wv[2], asf(v[2].y), wv[3] * asf(v[3].y));
                const float o2 = fmaf(wv[0], asf(v[0].z), wv[1] * asf(v[1].z)) + fmaf(wv[2], asf(v[2].z), wv[3] * asf(v[3].z));
                const float o3 = fmaf(wv[0], asf(v[0].w), wv[1] * asf(v[1].w)) + fmaf(wv[2], asf(v[2].w), wv[3] * asf(v[3].w));
                *reinterpret_cast<uint2*>(sgen + SM_ACT + gw * ACT_PITCH + (r ? SEG_O : SEG_Q) + lane * 8) =
                    make_uint2(pack_bf16(o0, o1), pack_bf16(o2, o3));
                bar_arrive(r ? BAR_O : BAR_Q, 384);
            }
            if (r) break;
            bar_sync(BAR_SGO, N_SGO);
            const int rh = misc[34] & 31;
            {
                const uint32_t side = near_side(misc);
                const int o = AR_O + slot_off((rh >> 2) * 16 + gw * 4) + (rh & 3) * 128 + lane * 4;
                pa = prm.arena + pick(o, side);
                pb = prm.arena + pick(o + 2048, side);
            }
            if (rh < 28) {
                const int rg = rh;
                const float* ph = prm.arena + AR_H + ((rg >> 1) * 8 + (lane >> 4) * 4) * 512 + gw * 128 + (rg & 1) * 64 + (lane & 15) * 4;
                uint4 v[4];
                gather4(v, ph, ph + 512, ph + 1024, ph + 1536, tag);
                float4 h = sum4(v);
                h.x += __shfl_xor_sync(0xffffffffu, h.x, 16); h.y += __shfl_xor_sync(0xffffffffu, h.y, 16);
                h.z += __shfl_xor_sync(0xffffffffu, h.z, 16); h.w += __shfl_xor_sync(0xffffffffu, h.w, 16);
                if (lane < 16)
                    *reinterpret_cast<uint2*>(sgen + SM_ACT + gw * ACT_PITCH + SEG_H + lane * 8) =
                        make_uint2(pack_bf16(fmaxf(h.x, 0.f), fmaxf(h.y, 0.f)), pack_bf16(fmaxf(h.z, 0.f), fmaxf(h.w, 0.f)));
                bar_arrive(BAR_H, 384);
            }
            {
                const float* ps = prm.arena + AR_XS + ((rh >> 2) * 16 + gw * 4 + (lane & 3)) * 8 + (rh & 2) * 2;
                uint4 v = ld4(ps);
                unsigned it = 0;
                while (__any_sync(0xffffffffu, badbits(v, tag) & 3u)) { v = ld4(ps); if (++it > SPIN_LIMIT) __trap(); }
                const float m = bf_hi((rh & 1) ? v.z : v.x);
                const float l = asf((rh & 1) ? v.w : v.y);
                float M = fmaxf(m, __shfl_xor_sync(0xffffffffu, m, 1));
                M = fmaxf(M, __shfl_xor_sync(0xffffffffu, M, 2));
                const float e = ex2((m - M) * 1.4426950408889634f);
                float L = e * l;
                L += __shfl_xor_sync(0xffffffffu, L, 1);
                L += __shfl_xor_sync(0xffffffffu, L, 2);
                const float wgt = __fdividef(e, L);
#pragma unroll
                for (int i = 0; i < 4; i++) wv[i] = __shfl_sync(0xffffffffu, wgt, i);
            }
        }
        return;
    }

    if (wix < 6 + NS) {
        const bool is_s = wix >= 6;
        if (wix == 6) { misc[lane] = 0xffffffffu; misc[33] = 0u; }
        if (wix == 5) {
            if (lane == 0) {
                unsigned epoch;
                asm volatile("ld.relaxed.gpu.global.u32 %0, [%1];" : "=r"(epoch) : "l"(prm.arena + AR_EPOCH) : "memory");
                misc[32] = epoch + 1;
            }
            __syncwarp();
            bar_arrive(BAR_XN, 448);
            bar_sync(BAR_RGO, 288);
            const uint32_t tg = misc[32];
            const float* pw = prm.arena + AR_XS + lane * 8;
            uint4 sw[4];
            gather4(sw, pw, pw + 256, pw + 512, pw + 768, tg);
            uint32_t n1 = 0, below = 0;
#pragma unroll
            for (int i = 0; i < 4; i++) {
                const uint32_t ones = __ballot_sync(0xffffffffu, sw[i].x & 4u);
                n1 += __popc(ones);
                below += __popc(ones & __ballot_sync(0xffffffffu, phase_key(i * 32 + lane) < phase_key(cta)));
            }
            if (lane == 0) {
                const uint32_t rank = near_side(misc) ? NCTA - n1 + below : phase_key(cta) - below;
                misc[35] = NCTA - n1;
                misc[34] = ((rank >> 6) * 2 + (rank & 1)) * 32 + ((rank & 63) >> 1);
            }
        }
        bar_sync(BAR_SGO, N_SGO);
        const uint32_t tag = misc[32];
        const int role = misc[34];
        const uint32_t side = near_side(misc);
        const bool odd = side != (uint32_t)(role >> 6);
        const int p = lane >> 2;
        const int o = slot_off((role & ~31) + p) + (role & 31) * 16 + (lane & 3) * 4 + (is_s ? AR_S : AR_F);
        const float* s0 = prm.arena + pick(o, side);
        const float* s1 = prm.arena + pick(o + 8192, side);
        const float* s2 = prm.arena + pick(o + 16384, side);
        const float* s3 = prm.arena + pick(o + 24576, side);
        const bool u16 = lane & 16, u8 = lane & 8;
        uint4 v[4];
        if (!is_s) {
            const bool skip3 = p >= 4;
            if (skip3) s3 = s0;
            bar_sync(BAR_FGO, 288);
            gather4(v, s0, s1, s2, s3, tag);
            if (skip3) v[3] = make_uint4(0u, 0u, 0u, 0u);
            const float4 a = sum4(v);
            const float e0 = (u16 ? a.z : a.x) + __shfl_xor_sync(0xffffffffu, u16 ? a.x : a.z, 16);
            const float e1 = (u16 ? a.w : a.y) + __shfl_xor_sync(0xffffffffu, u16 ? a.y : a.w, 16);
            float c = (u8 ? e1 : e0) + __shfl_xor_sync(0xffffffffu, u8 ? e0 : e1, 8);
            c += __shfl_xor_sync(0xffffffffu, c, 4);
            const float f = bf16r(c);
            misc[lane] = __float_as_uint(bf16r(__fdividef(f, 1.f + ex2(f * -1.4426950408889634f))));
        } else {
            const int oidx = (lane >> 3) * 512 + role * 4 + (lane & 3);
            const float xfin = __bfloat162float(prm.x[oidx]);
            const unsigned long long optr = __shfl_sync(0xffffffffu, (unsigned long long)(prm.out + oidx), lane);
            const uint32_t zero = tag >> 8;
            const uint32_t gaddr = sbase + SM_MISC + lane * 4;
            const bool bump = (cta | lane | zero) == 0;
            bar_sync(BAR_SREL, N_SREL);
            if (wix > 6) delay((wix - 6) * SSTAG);
            unsigned it = 0;
            uint32_t gate, done, b0 = 1, b1 = 1, b2 = 1, b3 = 1;
            float k0, k1, t0, t1;
            while (true) {
                if (b0 & 3u) v[0] = ld4(s0);
                if (b1 & 3u) v[1] = ld4(s1);
                if (b2 & 3u) v[2] = ld4(s2);
                if (b3 & 3u) v[3] = ld4(s3);
                b0 = badbits(v[0], tag); b1 = badbits(v[1], tag); b2 = badbits(v[2], tag); b3 = badbits(v[3], tag);
                const uint32_t bad = (b0 | b1) | (b2 | b3);
                asm volatile("ld.volatile.shared.u32 %0, [%1];" : "=r"(done) : "r"(sbase + SM_MISC + 33 * 4 + (bad & zero)) : "memory");
                asm volatile("ld.volatile.shared.u32 %0, [%1];" : "=r"(gate) : "r"(gaddr + (bad & zero)) : "memory");
                const float4 a = sum4(v);
                k0 = u16 ? a.z : a.x; k1 = u16 ? a.w : a.y;
                t0 = __shfl_xor_sync(0xffffffffu, u16 ? a.x : a.z, 16);
                t1 = __shfl_xor_sync(0xffffffffu, u16 ? a.y : a.w, 16);
                const bool again = __any_sync(0xffffffffu, bad & 3u);
                asm volatile("{\n .reg .pred p;\n setp.eq.u32 p, %1, 0;\n @p st.volatile.shared.u32 [%0], %2;\n}"
                             :: "r"(sbase + SM_MISC + 33 * 4), "r"((uint32_t)again), "r"(tag) : "memory");
                if (!again) break;
                if (done) return;
                if (++it > SPIN_LIMIT) __trap();
            }
            const float e0 = k0 + t0, e1 = k1 + t1;
            float c = (u8 ? e1 : e0) + __shfl_xor_sync(0xffffffffu, u8 ? e0 : e1, 8);
            if (done) return;
            c += __shfl_xor_sync(0xffffffffu, c, 4);
            it = 0;
            while (gate == 0xffffffffu) { gate = misc[lane]; if (++it > 16 * SPIN_LIMIT) __trap(); }
            const float res = xfin + bf16r(bf16r(c) * asf(gate));
            asm volatile("st.global.u16 [%0], %1;" :: "l"(optr), "h"((unsigned short)pack_bf16(res, 0.f)) : "memory");
            if (bump) *reinterpret_cast<unsigned*>(prm.arena + AR_EPOCH) = (tag == 3) ? 0u : tag;
        }
        if (odd) { clear4(s0); clear4(s1); clear4(s2); clear4(s3); }
        return;
    }

    const int warp = wix - (6 + NS);
    const int qslot = hkv * 16 + rlo * 4 + rhi, hslot = (hkv * 2 + (cta & 1)) * 8 + ((cta >> 1) & 7);
    {
        float* pr = prm.arena + pick(AR_O + slot_off(cta) + (warp >> 1) * 128, warp & 1);
        if (lane < 4) st2(pr + lane * 2, 0u, 0u);
        bar_sync(BAR_MMA, 256);
        delay(200);
        if (lane == 0) {
            uint32_t v, c1;
            const uint32_t c0 = clock32();
            asm volatile("atom.relaxed.gpu.global.add.u32 %0, [%1], 4;" : "=r"(v) : "l"(pr) : "memory");
            asm volatile("{\n .reg .pred p;\n setp.ne.u32 p, %1, 1;\n mov.u32 %0, 0;\n @p mov.u32 %0, %%clock;\n}" : "=r"(c1) : "r"(v));
            misc[40 + warp] = c1 - c0;
        }
        __syncwarp();
    }
    const int g = lane >> 2, t = lane & 3;
    Ring ring{bar_full, bar_empty, 0, 0u};
    const int lrow = lane & 7, lmat = lane >> 3;
    const uint32_t a_lane = (lrow + ((lmat >> 1) << 3)) * 128 + ((((warp & 3) * 2 + (lmat & 1)) ^ lrow) << 4);
    const uint32_t a_off = sbase + (warp >> 2) * 8192 + a_lane;
    const uint32_t b_off = sbase + SM_ACT + (lane & 3) * ACT_PITCH + lmat * 16;
    const bool hi = t >= 2;
    const int pofs = (t & 1) * 256 + warp * 16 + g + (t >> 1) * 8;
    float* const myslot = prm.arena + slot_off(cta);
    float* pubs = nullptr;
    bool has_w2 = false, both = false;
    bar_sync(BAR_XN, 448);
    const uint32_t tag = misc[32];

    float vs[4] = {0.f, 0.f, 0.f, 0.f};
#pragma unroll 1
    for (int sg = 0; sg < 5; sg++) {
        if (sg == 1) {
            if (warp == 0 && lane < 4) st2(prm.arena + AR_XS + cta * 8 + lane * 2, 0u, 0u);
            bar_sync(BAR_Q, 384);
            uint32_t qa[16];
            const uint8_t* qs = sgen + SM_ACT + (g & 3) * ACT_PITCH + SEG_Q + t * 4;
#pragma unroll
            for (int k = 0; k < 16; k++) qa[k] = *reinterpret_cast<const uint32_t*>(qs + k * 16);
            const uint32_t k_off = sbase + (warp * 8 + lrow) * 128;
            const uint32_t sw0 = (lmat ^ lrow) << 4, sw1 = ((lmat + 4) ^ lrow) << 4;
            float mx = -INFINITY;
            uint8_t* sdst = sgen + SM_ACT + g * ACT_PITCH + SEG_P + (warp * 8 + 2 * t) * 2;
#pragma unroll 1
            for (int it = 0; it < KT; it++) {
                ring.wait();
                const uint32_t tb = ring.slot * TILE_B + k_off;
                uint32_t b[16];
                ldsm4(tb + sw0, b); ldsm4(tb + sw1, b + 4); ldsm4(tb + 8192 + sw0, b + 8); ldsm4(tb + 8192 + sw1, b + 12);
                float c0[4] = {0.f, 0.f, 0.f, 0.f}, c1[4] = {0.f, 0.f, 0.f, 0.f};
#pragma unroll
                for (int k = 0; k < 8; k += 2) {
                    mma16816(c0, qa[2 * k], 0u, qa[2 * k + 1], 0u, b[2 * k], b[2 * k + 1]);
                    mma16816(c1, qa[2 * k + 2], 0u, qa[2 * k + 3], 0u, b[2 * k + 2], b[2 * k + 3]);
                }
                ring.release(lane);
                const float scale = 0.08838834764831845f;
                const uint32_t sp = pack_bf16(bf16r(c0[0] + c1[0]) * scale, bf16r(c0[1] + c1[1]) * scale);
                mx = fmaxf(mx, fmaxf(bf_lo(sp), bf_hi(sp)));
                if (lane < 16) *reinterpret_cast<uint32_t*>(sdst + it * 128) = sp;
            }
            mx = fmaxf(mx, __shfl_xor_sync(0xffffffffu, mx, 1));
            mx = fmaxf(mx, __shfl_xor_sync(0xffffffffu, mx, 2));
            if (lane < 16 && t == 0) reinterpret_cast<float*>(sgen + SM_WMAX)[warp * 4 + g] = mx;
            bar_sync(BAR_MMA, 256);
            const int head = warp >> 1;
            const float* wm = reinterpret_cast<const float*>(sgen + SM_WMAX) + head;
            float m = wm[0];
#pragma unroll
            for (int i = 1; i < 8; i++) m = fmaxf(m, wm[4 * i]);
            uint8_t* pp = sgen + SM_ACT + head * ACT_PITCH + SEG_P + (warp & 1) * 1024 + lane * 16;
            float l = 0.f;
#pragma unroll 1
            for (int h = 0; h < 2; h++) {
                const uint4 u = *reinterpret_cast<const uint4*>(pp + h * 512);
                uint32_t w[4] = {u.x, u.y, u.z, u.w};
#pragma unroll
                for (int i = 0; i < 4; i++) {
                    const float L2E = 1.4426950408889634f;
                    const float p0 = ex2((bf_lo(w[i]) - m) * L2E), p1 = ex2((bf_hi(w[i]) - m) * L2E);
                    l += p0 + p1;
                    w[i] = pack_bf16(p0, p1);
                }
                *reinterpret_cast<uint4*>(pp + h * 512) = make_uint4(w[0], w[1], w[2], w[3]);
            }
#pragma unroll
            for (int o = 16; o; o >>= 1) l += __shfl_xor_sync(0xffffffffu, l, o);
            if (lane == 0) reinterpret_cast<float*>(sgen + SM_LSUM)[warp] = l;
            bar_sync(BAR_MMA, 256);
            if ((warp & 1) && lane < 2) {
                const float* ls = reinterpret_cast<const float*>(sgen + SM_LSUM);
                st1(prm.arena + AR_XS + cta * 8 + head * 2 + lane, lane ? tagged(ls[warp - 1] + ls[warp], tag) : (__float_as_uint(m) | tag | (near_side(misc) << 2)));
            }
        }
        if ((sg == 2 && !has_w1) || (sg == 4 && !has_w2)) continue;
        const int i0 = (sg == 3) ? W1POS : (sg == 1) ? 0 : 32;
        const int i1 = (sg == 3) ? KT : (sg == 1) ? W1POS : (sg == 0) ? 34 : 33;
        const int seg = (sg == 0) ? SEG_XN + rhi * 256 : (sg == 2) ? SEG_XN + ((cta >> 1) & 7) * 128 : (sg == 4) ? SEG_H : SEG_P + i0 * 128;
        float* const pd = (sg == 0 ? prm.arena + AR_Q + qslot * 512 : sg == 2 ? prm.arena + AR_H + hslot * 512 : myslot + AR_O) + pofs;
        uint32_t ba = b_off + seg;
        float c0[4], c1[4];
#pragma unroll
        for (int k = 0; k < 4; k++) { c0[k] = sg == 3 ? vs[k] : 0.f; c1[k] = 0.f; }
        if (sg == 4) bar_sync(BAR_H, 384);
#pragma unroll 1
        for (int i = i0; i < i1; i++) {
            if (i == RGO) bar_arrive(BAR_RGO, 288);
            if (i == SGO) {
                bar_sync(BAR_SGO, N_SGO);
                const int role = misc[34], col = warp * 16 + g + (t >> 1) * 8;
                const int o = slot_off(role) + col * 4 + (t & 1) * 2;
                pubs = prm.arena + pick(AR_S + o, role >> 6);
                has_w2 = (role & 31) < 28;
                both = ((role >> 6) * 64 + (col >> 2) * 2 + ((role >> 5) & 1) >= (int)misc[35]) != (role >> 6);
            }
            if (i == CLRO) { st1(pd, 0u); st1(pd + 128, 0u); st1(pd + 1024, 0u); st1(pd + 1152, 0u); }
            if (i == CLRF && has_w2) { st2(other(pubs) - S_TO_F, 0u, 0u); st2_if(both, pubs - S_TO_F, 0u, 0u); }
            if (i == CLRS) { st2(pubs, 0u, 0u); st2_if(both, other(pubs), 0u, 0u); }
            uint32_t a[16], b[8];
            ldsm4(ba, b); ldsm4(ba + 64, b + 4);
            ring.wait();
            const uint32_t aa = a_off + ring.slot * TILE_B;
#pragma unroll
            for (int k = 0; k < 4; k++) ldsm4t(aa + k * 2048, a + 4 * k);
            mma16816(c0, a[0], a[1], a[2], a[3], b[0], b[1]);
            mma16816(c1, a[4], a[5], a[6], a[7], b[2], b[3]);
            mma16816(c0, a[8], a[9], a[10], a[11], b[4], b[5]);
            mma16816(c1, a[12], a[13], a[14], a[15], b[6], b[7]);
            ring.release(lane);
            ba += 128;
        }
        if (sg == 1) {
#pragma unroll
            for (int k = 0; k < 4; k++) vs[k] = c0[k] + c1[k];
            continue;
        }
        const uint32_t r0 = tagged(hi ? c0[2] + c1[2] : c0[0] + c1[0], tag), r1 = tagged(hi ? c0[3] + c1[3] : c0[1] + c1[1], tag);
        if (sg == 4) { st2(other(pubs) - S_TO_F, r0, r1); st2_if(both, pubs - S_TO_F, r0, r1); }
        else {
            st1(pd, r0); st1(pd + 128, r1);
            if (sg == 3) { st1(pd + 1024, r0); st1(pd + 1152, r1); }
            if (sg != 2) bar_arrive(sg ? BAR_VGO : BAR_QGO, 384);
        }
    }
    bar_arrive(BAR_FGO, 288);
    {
        uint32_t a[8], b[16];
        float c[4][4];
#pragma unroll
        for (int k = 0; k < 4; k++) { c[k][0] = 0.f; c[k][1] = 0.f; c[k][2] = 0.f; c[k][3] = 0.f; }
        const uint32_t ap_off = sbase + (warp >> 2) * 4096 + a_lane;
        bar_sync(BAR_O, 384);
#pragma unroll
        for (int k = 0; k < 4; k++) ldsm4(b_off + SEG_O + k * 64, b + 4 * k);
#pragma unroll
        for (int q = 0; q < 4; q++) {
            const uint32_t bq = (q & 1) ? bar_half + (q >> 1) * 8 : ring.full + ring.slot * 8;
            const uint32_t pq = (q & 1) ? 0u : ring.phase;
            const uint32_t aa = ap_off + ring.slot * TILE_B + (q & 1) * (TILE_B / 2);
            if (q >= 2) mbar_spin(bq, pq); else mbar_wait(bq, pq);
            ldsm4t(aa, a); ldsm4t(aa + 2048, a + 4);
            mma16816(c[(2 * q) & 3], a[0], a[1], a[2], a[3], b[4 * q], b[4 * q + 1]);
            mma16816(c[(2 * q + 1) & 3], a[4], a[5], a[6], a[7], b[4 * q + 2], b[4 * q + 3]);
            if (q & 1) ring.next();
        }
        const float r0 = ((hi ? c[0][2] : c[0][0]) + (hi ? c[1][2] : c[1][0])) + ((hi ? c[2][2] : c[2][0]) + (hi ? c[3][2] : c[3][0]));
        const float r1 = ((hi ? c[0][3] : c[0][1]) + (hi ? c[1][3] : c[1][1])) + ((hi ? c[2][3] : c[2][1]) + (hi ? c[3][3] : c[3][1]));
        const uint32_t u0 = tagged(r0, tag), u1 = tagged(r1, tag);
        st2(pubs, u0, u1);
        st2_if(both, other(pubs), u0, u1);
        bar_arrive(BAR_SREL, N_SREL);
    }
}

typedef CUresult (*EncodeFn)(CUtensorMap*, CUtensorMapDataType, cuuint32_t, void*, const cuuint64_t*, const cuuint64_t*,
                             const cuuint32_t*, const cuuint32_t*, CUtensorMapInterleave, CUtensorMapSwizzle,
                             CUtensorMapL2promotion, CUtensorMapFloatOOBfill);

void make_map(EncodeFn enc, CUtensorMap* m, const void* base, uint64_t rows, uint64_t cols, uint32_t box_rows) {
    cuuint64_t dims[3] = {64, rows, cols / 64};
    cuuint64_t strides[2] = {cols * 2, 128};
    cuuint32_t box[3] = {64, box_rows, 2};
    cuuint32_t es[3] = {1, 1, 1};
    enc(m, CU_TENSOR_MAP_DATA_TYPE_BFLOAT16, 3, const_cast<void*>(base), dims, strides, box, es,
        CU_TENSOR_MAP_INTERLEAVE_NONE, CU_TENSOR_MAP_SWIZZLE_128B, CU_TENSOR_MAP_L2_PROMOTION_L2_256B,
        CU_TENSOR_MAP_FLOAT_OOB_FILL_NONE);
}

}

extern "C" void kernel_launch(void* const* d_in, const int* in_sizes, int n_in, void* d_out, int out_size) {
    (void)in_sizes; (void)n_in; (void)out_size;
    static EncodeFn enc = nullptr;
    static void* arena_ptr = nullptr;
    if (!enc) {
        void* fn = nullptr;
        cudaDriverEntryPointQueryResult qr;
        cudaGetDriverEntryPoint("cuTensorMapEncodeTiled", &fn, cudaEnableDefault, &qr);
        enc = (EncodeFn)fn;
        cudaGetSymbolAddress(&arena_ptr, g_arena);
        cudaFuncSetAttribute(fused_decode_kernel, cudaFuncAttributeMaxDynamicSharedMemorySize, SM_TOTAL + 1024);
    }
    Params prm;
    make_map(enc, &prm.m[0], d_in[3], 512, 4096, 64);
    make_map(enc, &prm.m[1], d_in[6], 512, 1792, 64);
    make_map(enc, &prm.m[2], d_in[1], 4ull * 8 * 16384, 128, 64);
    make_map(enc, &prm.m[3], d_in[2], 4ull * 8 * 16384, 128, 64);
    make_map(enc, &prm.m[4], d_in[7], 1792, 512, 64);
    make_map(enc, &prm.m[5], d_in[4], 4096, 512, 32);
    prm.raw[0] = (const char*)d_in[2];
    prm.raw[1] = (const char*)d_in[7];
    prm.raw[2] = (const char*)d_in[4];
    prm.x = (const __nv_bfloat16*)d_in[0];
    prm.out = (__nv_bfloat16*)d_out;
    prm.arena = (float*)(((uintptr_t)arena_ptr + 0x200000ull) & ~0x1fffffull);
    fused_decode_kernel<<<NCTA, NTHREADS, SM_TOTAL + 1024>>>(prm);
}
```

```cpp
#include <cuda_runtime.h>
#include <cuda_bf16.h>
#include <cuda.h>
#include <stdint.h>

namespace {

constexpr int NCTA     = 128;
constexpr int NFFN     = 112;
constexpr int NSLOT    = 13;
constexpr int TILE_B   = 16384;
constexpr int KT       = 16;
constexpr int NS       = 3;
constexpr int NTHREADS = 448 + 32 * NS;

constexpr int TAU      = 657;
constexpr int LEAD     = 22;
constexpr int INFLIGHT = 8;
constexpr int TAILCAP  = 3;
constexpr int W1POS    = 6;
constexpr int QSLOT = 5;
constexpr int RGO   = 4;
constexpr int SGO   = 10;
constexpr int CLRO = 12, CLRF = 13, CLRS = 14;
constexpr unsigned SSTAG = 115;

constexpr int SEG_XN = 0;
constexpr int SEG_P  = 1024;
constexpr int SEG_H  = 3072;
constexpr int SEG_O  = 3200;
constexpr int SEG_Q  = 3456;
constexpr int ACT_PITCH = 3712 + 16;
constexpr int SM_ACT   = NSLOT * TILE_B;
constexpr int SM_WMAX  = SM_ACT + 4 * ACT_PITCH;
constexpr int SM_LSUM  = SM_WMAX + 128;
constexpr int SM_MISC  = SM_LSUM + 32;
constexpr int SM_BAR   = SM_MISC + 256;
constexpr int SM_TOTAL = SM_BAR + (2 * NSLOT + 2) * 8;
static_assert(SM_TOTAL + 1024 <= 232448, "smem");

constexpr int BAR_MMA = 1, BAR_XN = 2, BAR_Q = 3, BAR_H = 4, BAR_O = 5, BAR_VGO = 6, BAR_QGO = 7, BAR_SGO = 8,
              BAR_FGO = 9, BAR_SREL = 10, BAR_RGO = 11;
constexpr int N_SGO = 416 + 32 * NS, N_SREL = 256 + 32 * NS;

__device__ __align__(4096) float g_arena[1 << 21];
constexpr int AR_O = 0, AR_F = 131072, AR_S = 262144, AR_Q = 393216, AR_H = 458752;
constexpr int S_TO_F = AR_S - AR_F;
constexpr int AR_XS = AR_F + 62 * 2048;
constexpr int AR_EPOCH = AR_XS + 2048;
constexpr uint32_t HOME_MASK = (1u << 12) | (1u << 13) | (1u << 16) | (1u << 17) | (1u << 19);

struct Params {
    CUtensorMap m[6];
    const char* raw[4];
    const __nv_bfloat16* x;
    __nv_bfloat16* out;
    float* arena;
};

constexpr unsigned SPIN_LIMIT = 1u << 20;

__device__ __forceinline__ int phase_key(int cta) { return (((cta >> 2) * 13) & 31) * 4 + (cta & 3); }
__device__ __forceinline__ int slot_off(int producer) { return (producer >> 1) * 2048 + (producer & 1) * 512; }
__device__ __forceinline__ uint32_t parity(int off) { return __popc(((uint32_t)off << 2) & HOME_MASK) & 1u; }
__device__ __forceinline__ int pick(int off, uint32_t side) { return off + (int)((parity(off) ^ side) << 10); }

__device__ __forceinline__ void mbar_init(uint32_t bar, uint32_t cnt) {
    asm volatile("mbarrier.init.shared::cta.b64 [%0], %1;" :: "r"(bar), "r"(cnt) : "memory");
}
__device__ __forceinline__ void mbar_expect_tx(uint32_t bar, uint32_t bytes) {
    asm volatile("mbarrier.arrive.expect_tx.shared::cta.b64 _, [%0], %1;" :: "r"(bar), "r"(bytes) : "memory");
}
__device__ __forceinline__ void mbar_arrive(uint32_t bar) {
    asm volatile("mbarrier.arrive.shared::cta.b64 _, [%0];" :: "r"(bar) : "memory");
}
__device__ __forceinline__ bool mbar_test(uint32_t bar, uint32_t par) {
    uint32_t ok;
    asm volatile("{\n .reg .pred p;\n mbarrier.test_wait.parity.shared::cta.b64 p, [%1], %2;\n selp.u32 %0, 1, 0, p;\n}"
                 : "=r"(ok) : "r"(bar), "r"(par) : "memory");
    return ok;
}
__device__ __forceinline__ void mbar_wait(uint32_t bar, uint32_t par) {
    uint32_t ok, it = 0;
    while (true) {
        asm volatile("{\n .reg .pred p;\n mbarrier.try_wait.parity.shared::cta.b64 p, [%1], %2, %3;\n selp.u32 %0, 1, 0, p;\n}"
                     : "=r"(ok) : "r"(bar), "r"(par), "r"(10000) : "memory");
        if (ok) break;
        if (++it > SPIN_LIMIT) __trap();
    }
}
__device__ __forceinline__ void mbar_spin(uint32_t bar, uint32_t par) {
    uint32_t ok, it = 0;
    while (true) {
        asm volatile("{\n .reg .pred p;\n mbarrier.try_wait.parity.shared::cta.b64 p, [%1], %2;\n selp.u32 %0, 1, 0, p;\n}"
                     : "=r"(ok) : "r"(bar), "r"(par) : "memory");
        if (ok) break;
        if (++it > 16 * SPIN_LIMIT) __trap();
    }
}
__device__ __forceinline__ void tma_tile(uint32_t dst, const CUtensorMap* tm, int row, int half, uint32_t bar) {
    asm volatile("cp.async.bulk.tensor.3d.shared::cluster.global.mbarrier::complete_tx::bytes.L2::cache_hint [%0], [%1, {%3, %4, %5}], [%2], %6;"
                 :: "r"(dst), "l"(tm), "r"(bar), "r"(0), "r"(row), "r"(half), "l"(0x12F0000000000000ull) : "memory");
}
__device__ __forceinline__ void ldsm4(uint32_t addr, uint32_t* r) {
    asm volatile("ldmatrix.sync.aligned.m8n8.x4.shared.b16 {%0,%1,%2,%3}, [%4];"
                 : "=r"(r[0]), "=r"(r[1]), "=r"(r[2]), "=r"(r[3]) : "r"(addr) : "memory");
}
__device__ __forceinline__ void ldsm4t(uint32_t addr, uint32_t* r) {
    asm volatile("ldmatrix.sync.aligned.m8n8.x4.trans.shared.b16 {%0,%1,%2,%3}, [%4];"
                 : "=r"(r[0]), "=r"(r[1]), "=r"(r[2]), "=r"(r[3]) : "r"(addr) : "memory");
}
__device__ __forceinline__ void mma16816(float (&c)[4], uint32_t a0, uint32_t a1, uint32_t a2, uint32_t a3,
                                         uint32_t b0, uint32_t b1) {
    asm volatile("mma.sync.aligned.m16n8k16.row.col.f32.bf16.bf16.f32 {%0,%1,%2,%3}, {%4,%5,%6,%7}, {%8,%9}, {%0,%1,%2,%3};"
                 : "+f"(c[0]), "+f"(c[1]), "+f"(c[2]), "+f"(c[3])
                 : "r"(a0), "r"(a1), "r"(a2), "r"(a3), "r"(b0), "r"(b1));
}
__device__ __forceinline__ void bar_sync(int id, int n) { asm volatile("bar.sync %0, %1;" :: "r"(id), "r"(n) : "memory"); }
__device__ __forceinline__ void bar_arrive(int id, int n) { asm volatile("bar.arrive %0, %1;" :: "r"(id), "r"(n) : "memory"); }
__device__ __forceinline__ unsigned gtime32() { unsigned t; asm volatile("mov.u32 %0, %%globaltimer_lo;" : "=r"(t)); return t; }
__device__ __forceinline__ unsigned clock32() { unsigned t; asm volatile("mov.u32 %0, %%clock;" : "=r"(t)); return t; }
__device__ __forceinline__ void delay(unsigned clocks) { const unsigned c0 = clock32(); while (clock32() - c0 < clocks) {} }

__device__ __forceinline__ float bf16r(float v) {
    uint32_t d; asm("cvt.rn.bf16x2.f32 %0, %1, %2;" : "=r"(d) : "f"(v), "f"(0.f));
    return __uint_as_float(d);
}
__device__ __forceinline__ uint32_t pack_bf16(float lo, float hi) {
    uint32_t d; asm("cvt.rn.bf16x2.f32 %0, %1, %2;" : "=r"(d) : "f"(hi), "f"(lo));
    return d;
}
__device__ __forceinline__ float bf_lo(uint32_t u) { return __uint_as_float(u << 16); }
__device__ __forceinline__ float bf_hi(uint32_t u) { return __uint_as_float(u & 0xffff0000u); }
__device__ __forceinline__ float ex2(float v) { float r; asm("ex2.approx.ftz.f32 %0, %1;" : "=f"(r) : "f"(v)); return r; }
__device__ __forceinline__ float asf(uint32_t u) { return __uint_as_float(u); }

__device__ __forceinline__ uint32_t tagged(float v, uint32_t tag) { return (__float_as_uint(v) & ~3u) | tag; }
__device__ __forceinline__ void st1(float* p, uint32_t u) {
    asm volatile("st.relaxed.gpu.global.u32 [%0], %1;" :: "l"(p), "r"(u) : "memory");
}
__device__ __forceinline__ void st2(float* p, uint32_t u0, uint32_t u1) {
    asm volatile("st.relaxed.gpu.global.v2.u32 [%0], {%1, %2};" :: "l"(p), "r"(u0), "r"(u1) : "memory");
}
__device__ __forceinline__ void st2_if(bool c, float* p, uint32_t u0, uint32_t u1) {
    asm volatile("{\n .reg .pred p;\n setp.ne.u32 p, %3, 0;\n @p st.relaxed.gpu.global.v2.u32 [%0], {%1, %2};\n}"
                 :: "l"(p), "r"(u0), "r"(u1), "r"((uint32_t)c) : "memory");
}
__device__ __forceinline__ void clear4(const float* p) {
    asm volatile("st.relaxed.gpu.global.v4.u32 [%0], {%1,%1,%1,%1};" :: "l"(p), "r"(0u) : "memory");
}
__device__ __forceinline__ float* other(float* p) { return reinterpret_cast<float*>(reinterpret_cast<uintptr_t>(p) ^ 4096u); }
__device__ __forceinline__ uint4 ld4(const float* p) {
    uint4 v;
    asm volatile("ld.relaxed.gpu.global.v4.u32 {%0,%1,%2,%3}, [%4];" : "=r"(v.x), "=r"(v.y), "=r"(v.z), "=r"(v.w) : "l"(p) : "memory");
    return v;
}
__device__ __forceinline__ uint32_t badbits(const uint4& v, uint32_t tag) {
    uint32_t a, b;
    asm("lop3.b32 %0, %1, %2, %3, 0x7e;" : "=r"(a) : "r"(v.x), "r"(tag), "r"(v.y));
    asm("lop3.b32 %0, %1, %2, %3, 0x7e;" : "=r"(b) : "r"(v.z), "r"(tag), "r"(v.w));
    return a | b;
}
__device__ __forceinline__ void gather4(uint4 (&v)[4], const float* p0, const float* p1, const float* p2, const float* p3, uint32_t tag) {
    v[0] = ld4(p0); v[1] = ld4(p1); v[2] = ld4(p2); v[3] = ld4(p3);
    unsigned it = 0;
    while (true) {
        const uint32_t b0 = badbits(v[0], tag), b1 = badbits(v[1], tag), b2 = badbits(v[2], tag), b3 = badbits(v[3], tag);
        if (!__any_sync(0xffffffffu, ((b0 | b1) | (b2 | b3)) & 3u)) break;
        if (b0 & 3u) v[0] = ld4(p0);
        if (b1 & 3u) v[1] = ld4(p1);
        if (b2 & 3u) v[2] = ld4(p2);
        if (b3 & 3u) v[3] = ld4(p3);
        if (++it > SPIN_LIMIT) __trap();
    }
}
__device__ __forceinline__ float4 sum4(const uint4 (&v)[4]) {
    return make_float4((asf(v[0].x) + asf(v[1].x)) + (asf(v[2].x) + asf(v[3].x)), (asf(v[0].y) + asf(v[1].y)) + (asf(v[2].y) + asf(v[3].y)),
                       (asf(v[0].z) + asf(v[1].z)) + (asf(v[2].z) + asf(v[3].z)), (asf(v[0].w) + asf(v[1].w)) + (asf(v[2].w) + asf(v[3].w)));
}
__device__ __forceinline__ uint32_t near_side(volatile uint32_t* misc) {
    const uint32_t m0 = min(min(misc[40], misc[42]), min(misc[44], misc[46]));
    const uint32_t m1 = min(min(misc[41], misc[43]), min(misc[45], misc[47]));
    return m1 < m0;
}

struct Ring {
    uint32_t full, empty;
    int slot; uint32_t phase;
    __device__ __forceinline__ void wait() { mbar_wait(full + slot * 8, phase); }
    __device__ __forceinline__ void next() { if (++slot == NSLOT) { slot = 0; phase ^= 1; } }
    __device__ __forceinline__ void release(int lane) {
        __syncwarp();
        if (lane == 0) mbar_arrive(empty + slot * 8);
        next();
    }
};

__global__ void __launch_bounds__(NTHREADS, 1)
fused_decode_kernel(const __grid_constant__ Params prm) {
    extern __shared__ uint8_t smem_raw[];
    const uint32_t sbase = ((uint32_t)__cvta_generic_to_shared(smem_raw) + 1023u) & ~1023u;
    uint8_t* sgen = smem_raw + (sbase - (uint32_t)__cvta_generic_to_shared(smem_raw));
    const int cta = blockIdx.x;
    const int hkv = cta >> 4, rhi = (cta >> 2) & 3, rlo = cta & 3;
    const bool has_w1 = cta < NFFN;
    const uint32_t bar_full = sbase + SM_BAR, bar_empty = bar_full + NSLOT * 8, bar_half = bar_empty + NSLOT * 8;

    if (threadIdx.x == 224) asm volatile("prefetch.global.L2 [%0];" :: "l"(prm.raw[3] + rhi * (128 * 8192) + (hkv * 4 + rlo) * 256));
    if (threadIdx.x - 1u < 31u) return;
    if (threadIdx.x == 0) {
        const unsigned t0 = gtime32();
        mbar_init(bar_full, 1);
        asm volatile("fence.mbarrier_init.release.cluster;" ::: "memory");
        mbar_expect_tx(bar_full, TILE_B);
        tma_tile(sbase, &prm.m[0], rhi * 128, (hkv * 4 + rlo) * 2, bar_full);
#pragma unroll
        for (int i = 1; i < 2 * NSLOT + 2; i++) mbar_init(bar_full + i * 8, (i < NSLOT || i >= 2 * NSLOT) ? 1 : 8);
        asm volatile("fence.mbarrier_init.release.cluster;" ::: "memory");
        volatile uint32_t* prole = reinterpret_cast<volatile uint32_t*>(sgen + SM_MISC) + 34;
        *prole = 0xffffffffu;
        asm volatile("barrier.arrive %0, %1;" :: "n"(BAR_XN), "n"(448) : "memory");
        const int kvrow = (rhi * 8 + hkv) * 16384 + 12288 + rlo * 64;
        const int toff = ((phase_key(cta) >> 2) * TAU) / 32 - (LEAD * TAU) / 16;
        constexpr int P_W1 = 18 + W1POS, P_W2 = 35, P_END = 38;
        int slot = 1; uint32_t eph = 1;
        int fslot = 0; uint32_t fph = 0;
        int landed = 0, issued = 1;
        uint32_t role = 0;
#pragma unroll 1
        for (int v = 1; v < P_END; v++) {
            if (v == 31) {
                unsigned it = 0;
                while ((role = *prole) == 0xffffffffu) { if (++it > 16 * SPIN_LIMIT) __trap(); }
            }
            const int rh = role & 31, rc = role >> 5;
            const bool has_w2 = rh < 28;
            int mi, row, half;
            if (v == 1)          { mi = 0; row = rhi * 128 + 64; half = (hkv * 4 + rlo) * 2; }
            else if (v == P_W1)  { mi = 1; row = ((cta >> 1) & 7) * 64; half = (hkv * 2 + (cta & 1)) * 2; }
            else if (v < P_W2)   { const int j = v - 2 - (v > P_W1); mi = 2 + (j >> 4); row = kvrow + (j & 15) * 256; half = 0; }
            else if (v == P_W2)  { mi = 4; row = rh * 64; half = rc * 2; }
            else                 { mi = 5; row = rh * 128 + (v - P_W2 - 1) * 64; half = rc * 2; }
            if (v < 6) asm volatile("prefetch.tensormap [%0];" :: "l"(&prm.m[v]) : "memory");
            if (v == 10) asm volatile("cp.async.bulk.prefetch.L2.global [%0], 128;" :: "l"(prm.raw[0] + (size_t)kvrow * 256) : "memory");
            if (v == 31) {
                if (has_w2) asm volatile("cp.async.bulk.prefetch.L2.global [%0], 128;" :: "l"(prm.raw[1] + rh * 65536 + rc * 256) : "memory");
                asm volatile("cp.async.bulk.prefetch.L2.global [%0], 128;" :: "l"(prm.raw[2] + rh * 131072 + rc * 256) : "memory");
            }
            if ((v == P_W1 && !has_w1) || (v == P_W2 && !has_w2)) continue;
            const int need = issued + 1 - (v >= P_W2 ? TAILCAP : INFLIGHT);
            while (landed < need) {
                mbar_wait(bar_full + fslot * 8, fph);
                if (++fslot == NSLOT) { fslot = 0; fph ^= 1; }
                landed++;
            }
            if (issued >= NSLOT) mbar_wait(bar_empty + slot * 8, eph);
            {
                const int due = (v - (!has_w2 && v > P_W2)) * TAU + toff;
                int s2 = slot - 2; uint32_t par = eph ^ 1;
                if (s2 < 0) { s2 += NSLOT; par ^= 1; }
                while ((int)(gtime32() - t0) < due) {
                    if (v > 4 && mbar_test(bar_full + s2 * 8, par)) break;
                }
            }
            const uint32_t dst = sbase + slot * TILE_B, bf = bar_full + slot * 8;
            if (v > P_W2) {
                const uint32_t bh = bar_half + (v - P_W2 - 1) * 8;
                mbar_expect_tx(bf, TILE_B / 2);
                tma_tile(dst, &prm.m[5], row, half, bf);
                mbar_expect_tx(bh, TILE_B / 2);
                tma_tile(dst + TILE_B / 2, &prm.m[5], row + 32, half, bh);
            } else {
                mbar_expect_tx(bf, TILE_B);
                tma_tile(dst, &prm.m[mi], row, half, bf);
            }
            if (++slot == NSLOT) { slot = 0; eph ^= 1; }
            issued++;
        }
    }
    int tix;
    asm volatile("mov.u32 %0, %%tid.x;" : "=r"(tix));
    if (tix == 0) return;
    const int lane = tix & 31;
    const int wix = __shfl_sync(0xffffffffu, tix >> 5, 0);
    volatile uint32_t* misc = reinterpret_cast<volatile uint32_t*>(sgen + SM_MISC);

    if (wix < 5) {
        const int gw = wix - 1;
        {
            const uint4* xr = reinterpret_cast<const uint4*>(prm.x + gw * 512);
            const uint4 u0 = __ldg(xr + lane), u1 = __ldg(xr + 32 + lane);
            const uint32_t w[8] = {u0.x, u0.y, u0.z, u0.w, u1.x, u1.y, u1.z, u1.w};
            float s = 0.f;
#pragma unroll
            for (int i = 0; i < 8; i++) s += bf_lo(w[i]) + bf_hi(w[i]);
#pragma unroll
            for (int o = 16; o; o >>= 1) s += __shfl_xor_sync(0xffffffffu, s, o);
            const float mean = s * (1.f / 512.f);
            float vs = 0.f;
#pragma unroll
            for (int i = 0; i < 8; i++) { const float d0 = bf_lo(w[i]) - mean, d1 = bf_hi(w[i]) - mean; vs += d0 * d0 + d1 * d1; }
#pragma unroll
            for (int o = 16; o; o >>= 1) vs += __shfl_xor_sync(0xffffffffu, vs, o);
            const float mb = bf16r(mean);
            float den, rden;
            asm("sqrt.approx.f32 %0, %1;" : "=f"(den) : "f"(bf16r(bf16r(vs * (1.f / 512.f)) + 1e-5f)));
            asm("rcp.approx.f32 %0, %1;" : "=f"(rden) : "f"(bf16r(den)));
            uint32_t r[8];
#pragma unroll
            for (int i = 0; i < 8; i++) r[i] = pack_bf16(bf16r(bf_lo(w[i]) - mb) * rden, bf16r(bf_hi(w[i]) - mb) * rden);
            uint8_t* xs = sgen + SM_ACT + gw * ACT_PITCH + SEG_XN + lane * 16;
            *reinterpret_cast<uint4*>(xs) = make_uint4(r[0], r[1], r[2], r[3]);
            *reinterpret_cast<uint4*>(xs + 512) = make_uint4(r[4], r[5], r[6], r[7]);
        }
        bar_arrive(BAR_XN, 448);
        float wv[4] = {1.f, 1.f, 1.f, 1.f};
        const float* pa = prm.arena + AR_Q + (hkv * 16 + gw * 4) * 512 + rhi * 128 + lane * 4;
        const float* pb = pa + 1024;
#pragma unroll 1
        for (int r = 0; r < 2; r++) {
            bar_sync(r ? BAR_VGO : BAR_QGO, 384);
            const uint32_t tag = misc[32];
            if (r == 0) mbar_wait(bar_full + QSLOT * 8, 0);
            {
                uint4 v[4];
                gather4(v, pa, pa + 512, pb, pb + 512, tag);
                const float o0 = fmaf(wv[0], asf(v[0].x), wv[1] * asf(v[1].x)) + fmaf(wv[2], asf(v[2].x), wv[3] * asf(v[3].x));
                const float o1 = fmaf(wv[0], asf(v[0].y), wv[1] * asf(v[1].y)) + fmaf(wv[2], asf(v[2].y), wv[3] * asf(v[3].y));
                const float o2 = fmaf(wv[0], asf(v[0].z), wv[1] * asf(v[1].z)) + fmaf(wv[2], asf(v[2].z), wv[3] * asf(v[3].z));
                const float o3 = fmaf(wv[0], asf(v[0].w), wv[1] * asf(v[1].w)) + fmaf(wv[2], asf(v[2].w), wv[3] * asf(v[3].w));
                *reinterpret_cast<uint2*>(sgen + SM_ACT + gw * ACT_PITCH + (r ? SEG_O : SEG_Q) + lane * 8) =
                    make_uint2(pack_bf16(o0, o1), pack_bf16(o2, o3));
                bar_arrive(r ? BAR_O : BAR_Q, 384);
            }
            if (r) break;
            bar_sync(BAR_SGO, N_SGO);
            const int rh = misc[34] & 31;
            {
                const uint32_t side = near_side(misc);
                const int o = AR_O + slot_off((rh >> 2) * 16 + gw * 4) + (rh & 3) * 128 + lane * 4;
                pa = prm.arena + pick(o, side);
                pb = prm.arena + pick(o + 2048, side);
            }
            if (rh < 28) {
                const int rg = rh;
                const float* ph = prm.arena + AR_H + ((rg >> 1) * 8 + (lane >> 4) * 4) * 512 + gw * 128 + (rg & 1) * 64 + (lane & 15) * 4;
                uint4 v[4];
                gather4(v, ph, ph + 512, ph + 1024, ph + 1536, tag);
                float4 h = sum4(v);
                h.x += __shfl_xor_sync(0xffffffffu, h.x, 16); h.y += __shfl_xor_sync(0xffffffffu, h.y, 16);
                h.z += __shfl_xor_sync(0xffffffffu, h.z, 16); h.w += __shfl_xor_sync(0xffffffffu, h.w, 16);
                if (lane < 16)
                    *reinterpret_cast<uint2*>(sgen + SM_ACT + gw * ACT_PITCH + SEG_H + lane * 8) =
                        make_uint2(pack_bf16(fmaxf(h.x, 0.f), fmaxf(h.y, 0.f)), pack_bf16(fmaxf(h.z, 0.f), fmaxf(h.w, 0.f)));
                bar_arrive(BAR_H, 384);
            }
            {
                const float* ps = prm.arena + AR_XS + ((rh >> 2) * 16 + gw * 4 + (lane & 3)) * 8 + (rh & 2) * 2;
                uint4 v = ld4(ps);
                unsigned it = 0;
                while (__any_sync(0xffffffffu, badbits(v, tag) & 3u)) { v = ld4(ps); if (++it > SPIN_LIMIT) __trap(); }
                const float m = bf_hi((rh & 1) ? v.z : v.x);
                const float l = asf((rh & 1) ? v.w : v.y);
                float M = fmaxf(m, __shfl_xor_sync(0xffffffffu, m, 1));
                M = fmaxf(M, __shfl_xor_sync(0xffffffffu, M, 2));
                const float e = ex2((m - M) * 1.4426950408889634f);
                float L = e * l;
                L += __shfl_xor_sync(0xffffffffu, L, 1);
                L += __shfl_xor_sync(0xffffffffu, L, 2);
                const float wgt = __fdividef(e, L);
#pragma unroll
                for (int i = 0; i < 4; i++) wv[i] = __shfl_sync(0xffffffffu, wgt, i);
            }
        }
        return;
    }

    if (wix < 6 + NS) {
        const bool is_s = wix >= 6;
        if (wix == 6) { misc[lane] = 0xffffffffu; misc[33] = 0u; }
        if (wix == 5) {
            if (lane == 0) {
                unsigned epoch;
                asm volatile("ld.relaxed.gpu.global.u32 %0, [%1];" : "=r"(epoch) : "l"(prm.arena + AR_EPOCH) : "memory");
                misc[32] = epoch + 1;
            }
            __syncwarp();
            bar_arrive(BAR_XN, 448);
            bar_sync(BAR_RGO, 288);
            const uint32_t tg = misc[32];
            const float* pw = prm.arena + AR_XS + lane * 8;
            uint4 sw[4];
            gather4(sw, pw, pw + 256, pw + 512, pw + 768, tg);
            uint32_t n1 = 0, below = 0;
#pragma unroll
            for (int i = 0; i < 4; i++) {
                const uint32_t ones = __ballot_sync(0xffffffffu, sw[i].x & 4u);
                n1 += __popc(ones);
                below += __popc(ones & __ballot_sync(0xffffffffu, phase_key(i * 32 + lane) < phase_key(cta)));
            }
            if (lane == 0) {
                const uint32_t rank = near_side(misc) ? NCTA - n1 + below : phase_key(cta) - below;
                misc[35] = NCTA - n1;
                misc[34] = ((rank >> 6) * 2 + (rank & 1)) * 32 + ((rank & 63) >> 1);
            }
        }
        bar_sync(BAR_SGO, N_SGO);
        const uint32_t tag = misc[32];
        const int role = misc[34];
        const uint32_t side = near_side(misc);
        const bool odd = side != (uint32_t)(role >> 6);
        const int p = lane >> 2;
        const int o = slot_off((role & ~31) + p) + (role & 31) * 16 + (lane & 3) * 4 + (is_s ? AR_S : AR_F);
        const float* s0 = prm.arena + pick(o, side);
        const float* s1 = prm.arena + pick(o + 8192, side);
        const float* s2 = prm.arena + pick(o + 16384, side);
        const float* s3 = prm.arena + pick(o + 24576, side);
        const bool u16 = lane & 16, u8 = lane & 8;
        uint4 v[4];
        if (!is_s) {
            const bool skip3 = p >= 4;
            if (skip3) s3 = s0;
            bar_sync(BAR_FGO, 288);
            gather4(v, s0, s1, s2, s3, tag);
            if (skip3) v[3] = make_uint4(0u, 0u, 0u, 0u);
            const float4 a = sum4(v);
            const float e0 = (u16 ? a.z : a.x) + __shfl_xor_sync(0xffffffffu, u16 ? a.x : a.z, 16);
            const float e1 = (u16 ? a.w : a.y) + __shfl_xor_sync(0xffffffffu, u16 ? a.y : a.w, 16);
            float c = (u8 ? e1 : e0) + __shfl_xor_sync(0xffffffffu, u8 ? e0 : e1, 8);
            c += __shfl_xor_sync(0xffffffffu, c, 4);
            const float f = bf16r(c);
            misc[lane] = __float_as_uint(bf16r(__fdividef(f, 1.f + ex2(f * -1.4426950408889634f))));
        } else {
            const int oidx = (lane >> 3) * 512 + role * 4 + (lane & 3);
            const float xfin = __bfloat162float(prm.x[oidx]);
            const unsigned long long optr = __shfl_sync(0xffffffffu, (unsigned long long)(prm.out + oidx), lane);
            const uint32_t zero = tag >> 8;
            const uint32_t gaddr = sbase + SM_MISC + lane * 4;
            const bool bump = (cta | lane | zero) == 0;
            bar_sync(BAR_SREL, N_SREL);
            if (wix > 6) delay((wix - 6) * SSTAG);
            unsigned it = 0;
            uint32_t gate, done, b0 = 1, b1 = 1, b2 = 1, b3 = 1;
            float k0, k1, t0, t1;
            while (true) {
                if (b0 & 3u) v[0] = ld4(s0);
                if (b1 & 3u) v[1] = ld4(s1);
                if (b2 & 3u) v[2] = ld4(s2);
                if (b3 & 3u) v[3] = ld4(s3);
                b0 = badbits(v[0], tag); b1 = badbits(v[1], tag); b2 = badbits(v[2], tag); b3 = badbits(v[3], tag);
                const uint32_t bad = (b0 | b1) | (b2 | b3);
                asm volatile("ld.volatile.shared.u32 %0, [%1];" : "=r"(done) : "r"(sbase + SM_MISC + 33 * 4 + (bad & zero)) : "memory");
                asm volatile("ld.volatile.shared.u32 %0, [%1];" : "=r"(gate) : "r"(gaddr + (bad & zero)) : "memory");
                const float4 a = sum4(v);
                k0 = u16 ? a.z : a.x; k1 = u16 ? a.w : a.y;
                t0 = __shfl_xor_sync(0xffffffffu, u16 ? a.x : a.z, 16);
                t1 = __shfl_xor_sync(0xffffffffu, u16 ? a.y : a.w, 16);
                const bool again = __any_sync(0xffffffffu, bad & 3u);
                asm volatile("{\n .reg .pred p;\n setp.eq.u32 p, %1, 0;\n @p st.volatile.shared.u32 [%0], %2;\n}"
                             :: "r"(sbase + SM_MISC + 33 * 4), "r"((uint32_t)again), "r"(tag) : "memory");
                if (!again) break;
                if (done) return;
                if (++it > SPIN_LIMIT) __trap();
            }
            const float e0 = k0 + t0, e1 = k1 + t1;
            float c = (u8 ? e1 : e0) + __shfl_xor_sync(0xffffffffu, u8 ? e0 : e1, 8);
            if (done) return;
            c += __shfl_xor_sync(0xffffffffu, c, 4);
            it = 0;
            while (gate == 0xffffffffu) { gate = misc[lane]; if (++it > 16 * SPIN_LIMIT) __trap(); }
            const float res = xfin + bf16r(bf16r(c) * asf(gate));
            asm volatile("st.global.u16 [%0], %1;" :: "l"(optr), "h"((unsigned short)pack_bf16(res, 0.f)) : "memory");
            if (bump) *reinterpret_cast<unsigned*>(prm.arena + AR_EPOCH) = (tag == 3) ? 0u : tag;
        }
        if (odd) { clear4(s0); clear4(s1); clear4(s2); clear4(s3); }
        return;
    }

    const int warp = wix - (6 + NS);
    const int qslot = hkv * 16 + rlo * 4 + rhi, hslot = (hkv * 2 + (cta & 1)) * 8 + ((cta >> 1) & 7);
    {
        float* pr = prm.arena + pick(AR_O + slot_off(cta) + (warp >> 1) * 128, warp & 1);
        if (lane < 4) st2(pr + lane * 2, 0u, 0u);
        bar_sync(BAR_MMA, 256);
        delay(200);
        if (lane == 0) {
            uint32_t v, c1;
            const uint32_t c0 = clock32();
            asm volatile("atom.relaxed.gpu.global.add.u32 %0, [%1], 4;" : "=r"(v) : "l"(pr) : "memory");
            asm volatile("{\n .reg .pred p;\n setp.ne.u32 p, %1, 1;\n mov.u32 %0, 0;\n @p mov.u32 %0, %%clock;\n}" : "=r"(c1) : "r"(v));
            misc[40 + warp] = c1 - c0;
        }
        __syncwarp();
    }
    const int g = lane >> 2, t = lane & 3;
    Ring ring{bar_full, bar_empty, 0, 0u};
    const int lrow = lane & 7, lmat = lane >> 3;
    const uint32_t a_lane = (lrow + ((lmat >> 1) << 3)) * 128 + ((((warp & 3) * 2 + (lmat & 1)) ^ lrow) << 4);
    const uint32_t a_off = sbase + (warp >> 2) * 8192 + a_lane;
    const uint32_t b_off = sbase + SM_ACT + (lane & 3) * ACT_PITCH + lmat * 16;
    const bool hi = t >= 2;
    const int pofs = (t & 1) * 256 + warp * 16 + g + (t >> 1) * 8;
    float* const myslot = prm.arena + slot_off(cta);
    float* pubs = nullptr;
    bool has_w2 = false, both = false;
    bar_sync(BAR_XN, 448);
    const uint32_t tag = misc[32];

    float vs[4] = {0.f, 0.f, 0.f, 0.f};
#pragma unroll 1
    for (int sg = 0; sg < 5; sg++) {
        if (sg == 1) {
            if (warp == 0 && lane < 4) st2(prm.arena + AR_XS + cta * 8 + lane * 2, 0u, 0u);
            bar_sync(BAR_Q, 384);
            uint32_t qa[16];
            const uint8_t* qs = sgen + SM_ACT + (g & 3) * ACT_PITCH + SEG_Q + t * 4;
#pragma unroll
            for (int k = 0; k < 16; k++) qa[k] = *reinterpret_cast<const uint32_t*>(qs + k * 16);
            const uint32_t k_off = sbase + (warp * 8 + lrow) * 128;
            const uint32_t sw0 = (lmat ^ lrow) << 4, sw1 = ((lmat + 4) ^ lrow) << 4;
            float mx = -INFINITY;
            uint8_t* sdst = sgen + SM_ACT + g * ACT_PITCH + SEG_P + (warp * 8 + 2 * t) * 2;
#pragma unroll 1
            for (int it = 0; it < KT; it++) {
                ring.wait();
                const uint32_t tb = ring.slot * TILE_B + k_off;
                uint32_t b[16];
                ldsm4(tb + sw0, b); ldsm4(tb + sw1, b + 4); ldsm4(tb + 8192 + sw0, b + 8); ldsm4(tb + 8192 + sw1, b + 12);
                float c0[4] = {0.f, 0.f, 0.f, 0.f}, c1[4] = {0.f, 0.f, 0.f, 0.f};
#pragma unroll
                for (int k = 0; k < 8; k += 2) {
                    mma16816(c0, qa[2 * k], 0u, qa[2 * k + 1], 0u, b[2 * k], b[2 * k + 1]);
                    mma16816(c1, qa[2 * k + 2], 0u, qa[2 * k + 3], 0u, b[2 * k + 2], b[2 * k + 3]);
                }
                ring.release(lane);
                const float scale = 0.08838834764831845f;
                const uint32_t sp = pack_bf16(bf16r(c0[0] + c1[0]) * scale, bf16r(c0[1] + c1[1]) * scale);
                mx = fmaxf(mx, fmaxf(bf_lo(sp), bf_hi(sp)));
                if (lane < 16) *reinterpret_cast<uint32_t*>(sdst + it * 128) = sp;
            }
            mx = fmaxf(mx, __shfl_xor_sync(0xffffffffu, mx, 1));
            mx = fmaxf(mx, __shfl_xor_sync(0xffffffffu, mx, 2));
            if (lane < 16 && t == 0) reinterpret_cast<float*>(sgen + SM_WMAX)[warp * 4 + g] = mx;
            bar_sync(BAR_MMA, 256);
            const int head = warp >> 1;
            const float* wm = reinterpret_cast<const float*>(sgen + SM_WMAX) + head;
            float m = wm[0];
#pragma unroll
            for (int i = 1; i < 8; i++) m = fmaxf(m, wm[4 * i]);
            uint8_t* pp = sgen + SM_ACT + head * ACT_PITCH + SEG_P + (warp & 1) * 1024 + lane * 16;
            float l = 0.f;
#pragma unroll 1
            for (int h = 0; h < 2; h++) {
                const uint4 u = *reinterpret_cast<const uint4*>(pp + h * 512);
                uint32_t w[4] = {u.x, u.y, u.z, u.w};
#pragma unroll
                for (int i = 0; i < 4; i++) {
                    const float L2E = 1.4426950408889634f;
                    const float p0 = ex2((bf_lo(w[i]) - m) * L2E), p1 = ex2((bf_hi(w[i]) - m) * L2E);
                    l += p0 + p1;
                    w[i] = pack_bf16(p0, p1);
                }
                *reinterpret_cast<uint4*>(pp + h * 512) = make_uint4(w[0], w[1], w[2], w[3]);
            }
#pragma unroll
            for (int o = 16; o; o >>= 1) l += __shfl_xor_sync(0xffffffffu, l, o);
            if (lane == 0) reinterpret_cast<float*>(sgen + SM_LSUM)[warp] = l;
            bar_sync(BAR_MMA, 256);
            if ((warp & 1) && lane < 2) {
                const float* ls = reinterpret_cast<const float*>(sgen + SM_LSUM);
                st1(prm.arena + AR_XS + cta * 8 + head * 2 + lane, lane ? tagged(ls[warp - 1] + ls[warp], tag) : (__float_as_uint(m) | tag | (near_side(misc) << 2)));
            }
        }
        if ((sg == 2 && !has_w1) || (sg == 4 && !has_w2)) continue;
        const int i0 = (sg == 3) ? W1POS : (sg == 1) ? 0 : 32;
        const int i1 = (sg == 3) ? KT : (sg == 1) ? W1POS : (sg == 0) ? 34 : 33;
        const int seg = (sg == 0) ? SEG_XN + rhi * 256 : (sg == 2) ? SEG_XN + ((cta >> 1) & 7) * 128 : (sg == 4) ? SEG_H : SEG_P + i0 * 128;
        float* const pd = (sg == 0 ? prm.arena + AR_Q + qslot * 512 : sg == 2 ? prm.arena + AR_H + hslot * 512 : myslot + AR_O) + pofs;
        uint32_t ba = b_off + seg;
        float c0[4], c1[4];
#pragma unroll
        for (int k = 0; k < 4; k++) { c0[k] = sg == 3 ? vs[k] : 0.f; c1[k] = 0.f; }
        if (sg == 4) bar_sync(BAR_H, 384);
#pragma unroll 1
        for (int i = i0; i < i1; i++) {
            if (i == RGO) bar_arrive(BAR_RGO, 288);
            if (i == SGO) {
                bar_sync(BAR_SGO, N_SGO);
                const int role = misc[34], col = warp * 16 + g + (t >> 1) * 8;
                const int o = slot_off(role) + col * 4 + (t & 1) * 2;
                pubs = prm.arena + pick(AR_S + o, role >> 6);
                has_w2 = (role & 31) < 28;
                both = ((role >> 6) * 64 + (col >> 2) * 2 + ((role >> 5) & 1) >= (int)misc[35]) != (role >> 6);
            }
            if (i == CLRO) { st1(pd, 0u); st1(pd + 128, 0u); st1(pd + 1024, 0u); st1(pd + 1152, 0u); }
            if (i == CLRF && has_w2) { st2(other(pubs) - S_TO_F, 0u, 0u); st2_if(both, pubs - S_TO_F, 0u, 0u); }
            if (i == CLRS) { st2(pubs, 0u, 0u); st2_if(both, other(pubs), 0u, 0u); }
            uint32_t a[16], b[8];
            ldsm4(ba, b); ldsm4(ba + 64, b + 4);
            ring.wait();
            const uint32_t aa = a_off + ring.slot * TILE_B;
#pragma unroll
            for (int k = 0; k < 4; k++) ldsm4t(aa + k * 2048, a + 4 * k);
            mma16816(c0, a[0], a[1], a[2], a[3], b[0], b[1]);
            mma16816(c1, a[4], a[5], a[6], a[7], b[2], b[3]);
            mma16816(c0, a[8], a[9], a[10], a[11], b[4], b[5]);
            mma16816(c1, a[12], a[13], a[14], a[15], b[6], b[7]);
            ring.release(lane);
            ba += 128;
        }
        if (sg == 1) {
#pragma unroll
            for (int k = 0; k < 4; k++) vs[k] = c0[k] + c1[k];
            continue;
        }
        const uint32_t r0 = tagged(hi ? c0[2] + c1[2] : c0[0] + c1[0], tag), r1 = tagged(hi ? c0[3] + c1[3] : c0[1] + c1[1], tag);
        if (sg == 4) { st2(other(pubs) - S_TO_F, r0, r1); st2_if(both, pubs - S_TO_F, r0, r1); }
        else {
            st1(pd, r0); st1(pd + 128, r1);
            if (sg == 3) { st1(pd + 1024, r0); st1(pd + 1152, r1); }
            if (sg != 2) bar_arrive(sg ? BAR_VGO : BAR_QGO, 384);
        }
    }
    bar_arrive(BAR_FGO, 288);
    {
        uint32_t a[8], b[16];
        float c[4][4];
#pragma unroll
        for (int k = 0; k < 4; k++) { c[k][0] = 0.f; c[k][1] = 0.f; c[k][2] = 0.f; c[k][3] = 0.f; }
        const uint32_t ap_off = sbase + (warp >> 2) * 4096 + a_lane;
        bar_sync(BAR_O, 384);
#pragma unroll
        for (int k = 0; k < 4; k++) ldsm4(b_off + SEG_O + k * 64, b + 4 * k);
#pragma unroll
        for (int q = 0; q < 4; q++) {
            const uint32_t bq = (q & 1) ? bar_half + (q >> 1) * 8 : ring.full + ring.slot * 8;
            const uint32_t pq = (q & 1) ? 0u : ring.phase;
            const uint32_t aa = ap_off + ring.slot * TILE_B + (q & 1) * (TILE_B / 2);
            if (q == 3) bar_arrive(BAR_SREL, N_SREL);
            if (q >= 2) mbar_spin(bq, pq); else mbar_wait(bq, pq);
            ldsm4t(aa, a); ldsm4t(aa + 2048, a + 4);
            mma16816(c[(2 * q) & 3], a[0], a[1], a[2], a[3], b[4 * q], b[4 * q + 1]);
            mma16816(c[(2 * q + 1) & 3], a[4], a[5], a[6], a[7], b[4 * q + 2], b[4 * q + 3]);
            if (q & 1) ring.next();
        }
        const float r0 = ((hi ? c[0][2] : c[0][0]) + (hi ? c[1][2] : c[1][0])) + ((hi ? c[2][2] : c[2][0]) + (hi ? c[3][2] : c[3][0]));
        const float r1 = ((hi ? c[0][3] : c[0][1]) + (hi ? c[1][3] : c[1][1])) + ((hi ? c[2][3] : c[2][1]) + (hi ? c[3][3] : c[3][1]));
        const uint32_t u0 = tagged(r0, tag), u1 = tagged(r1, tag);
        st2(pubs, u0, u1);
        st2_if(both, other(pubs), u0, u1);
    }
}

typedef CUresult (*EncodeFn)(CUtensorMap*, CUtensorMapDataType, cuuint32_t, void*, const cuuint64_t*, const cuuint64_t*,
                             const cuuint32_t*, const cuuint32_t*, CUtensorMapInterleave, CUtensorMapSwizzle,
                             CUtensorMapL2promotion, CUtensorMapFloatOOBfill);

void make_map(EncodeFn enc, CUtensorMap* m, const void* base, uint64_t rows, uint64_t cols, uint32_t box_rows) {
    cuuint64_t dims[3] = {64, rows, cols / 64};
    cuuint64_t strides[2] = {cols * 2, 128};
    cuuint32_t box[3] = {64, box_rows, 2};
    cuuint32_t es[3] = {1, 1, 1};
    enc(m, CU_TENSOR_MAP_DATA_TYPE_BFLOAT16, 3, const_cast<void*>(base), dims, strides, box, es,
        CU_TENSOR_MAP_INTERLEAVE_NONE, CU_TENSOR_MAP_SWIZZLE_128B, CU_TENSOR_MAP_L2_PROMOTION_L2_256B,
        CU_TENSOR_MAP_FLOAT_OOB_FILL_NONE);
}

}

extern "C" void kernel_launch(void* const* d_in, const int* in_sizes, int n_in, void* d_out, int out_size) {
    (void)in_sizes; (void)n_in; (void)out_size;
    static EncodeFn enc = nullptr;
    static void* arena_ptr = nullptr;
    if (!enc) {
        void* fn = nullptr;
        cudaDriverEntryPointQueryResult qr;
        cudaGetDriverEntryPoint("cuTensorMapEncodeTiled", &fn, cudaEnableDefault, &qr);
        enc = (EncodeFn)fn;
        cudaGetSymbolAddress(&arena_ptr, g_arena);
        cudaFuncSetAttribute(fused_decode_kernel, cudaFuncAttributeMaxDynamicSharedMemorySize, SM_TOTAL + 1024);
    }
    Params prm;
    make_map(enc, &prm.m[0], d_in[3], 512, 4096, 64);
    make_map(enc, &prm.m[1], d_in[6], 512, 1792, 64);
    make_map(enc, &prm.m[2], d_in[1], 4ull * 8 * 16384, 128, 64);
    make_map(enc, &prm.m[3], d_in[2], 4ull * 8 * 16384, 128, 64);
    make_map(enc, &prm.m[4], d_in[7], 1792, 512, 64);
    make_map(enc, &prm.m[5], d_in[4], 4096, 512, 32);
    prm.raw[0] = (const char*)d_in[2];
    prm.raw[1] = (const char*)d_in[7];
    prm.raw[2] = (const char*)d_in[4];
    prm.raw[3] = (const char*)d_in[3];
    prm.x = (const __nv_bfloat16*)d_in[0];
    prm.out = (__nv_bfloat16*)d_out;
    prm.arena = (float*)(((uintptr_t)arena_ptr + 0x600000ull) & ~0x1fffffull);
    fused_decode_kernel<<<NCTA, NTHREADS, SM_TOTAL + 1024>>>(prm);
}
```

```cpp
#include <cuda_runtime.h>
#include <cuda_bf16.h>
#include <cuda.h>
#include <stdint.h>

namespace {

constexpr int NCTA     = 128;
constexpr int NFFN     = 112;
constexpr int NSLOT    = 13;
constexpr int TILE_B   = 16384;
constexpr int KT       = 16;
constexpr int NTHREADS = 448;

constexpr int TAU      = 658;
constexpr int LEAD     = 22;
constexpr int INFLIGHT = 8;
constexpr int W1POS    = 6;
constexpr int QSLOT = 5;
constexpr int RGO   = 4;
constexpr int SGO   = 10;
constexpr int CLRO  = 12;

constexpr int SEG_XN = 0;
constexpr int SEG_P  = 1024;
constexpr int SEG_H  = 3072;
constexpr int SEG_O  = 3200;
constexpr int SEG_Q  = 3456;
constexpr int ACT_PITCH = 3712 + 16;
constexpr int SM_ACT   = NSLOT * TILE_B;
constexpr int SM_WMAX  = SM_ACT + 4 * ACT_PITCH;
constexpr int SM_LSUM  = SM_WMAX + 128;
constexpr int SM_MISC  = SM_LSUM + 32;
constexpr int SM_BAR   = SM_MISC + 256;
constexpr int SM_TOTAL = SM_BAR + (2 * NSLOT + 2) * 8;
static_assert(SM_TOTAL + 1024 <= 232448, "smem");

constexpr int BAR_MMA = 1, BAR_XN = 2, BAR_Q = 3, BAR_H = 4, BAR_O = 5, BAR_VGO = 6, BAR_QGO = 7, BAR_SGO = 8,
              BAR_RGO = 9;
constexpr int N_SGO = 416;

__device__ __align__(4096) float g_arena[1 << 21];
constexpr int AR_O = 0, AR_C = 262144, AR_Q = 393216, AR_H = 458752;
constexpr int AR_XS = 258048;
constexpr int AR_EPOCH = AR_XS + 2048;
constexpr uint32_t HOME_MASK = (1u << 12) | (1u << 13) | (1u << 16) | (1u << 17) | (1u << 19);

struct Params {
    CUtensorMap m[6];
    const char* raw[4];
    const __nv_bfloat16* x;
    __nv_bfloat16* out;
    float* arena;
};

constexpr unsigned SPIN_LIMIT = 1u << 20;

__device__ __forceinline__ int phase_key(int cta) { return (((cta >> 2) * 13) & 31) * 4 + (cta & 3); }
__device__ __forceinline__ int slot_off(int producer) { return (producer >> 1) * 2048 + (producer & 1) * 512; }
__device__ __forceinline__ uint32_t parity(int off) { return __popc(((uint32_t)off << 2) & HOME_MASK) & 1u; }
__device__ __forceinline__ int pick(int off, uint32_t side) { return off + (int)((parity(off) ^ side) << 10); }

__device__ __forceinline__ void mbar_init(uint32_t bar, uint32_t cnt) {
    asm volatile("mbarrier.init.shared::cta.b64 [%0], %1;" :: "r"(bar), "r"(cnt) : "memory");
}
__device__ __forceinline__ void mbar_expect_tx(uint32_t bar, uint32_t bytes) {
    asm volatile("mbarrier.arrive.expect_tx.shared::cta.b64 _, [%0], %1;" :: "r"(bar), "r"(bytes) : "memory");
}
__device__ __forceinline__ void mbar_arrive(uint32_t bar) {
    asm volatile("mbarrier.arrive.shared::cta.b64 _, [%0];" :: "r"(bar) : "memory");
}
__device__ __forceinline__ bool mbar_test(uint32_t bar, uint32_t par) {
    uint32_t ok;
    asm volatile("{\n .reg .pred p;\n mbarrier.test_wait.parity.shared::cta.b64 p, [%1], %2;\n selp.u32 %0, 1, 0, p;\n}"
                 : "=r"(ok) : "r"(bar), "r"(par) : "memory");
    return ok;
}
__device__ __forceinline__ void mbar_wait(uint32_t bar, uint32_t par) {
    uint32_t ok, it = 0;
    while (true) {
        asm volatile("{\n .reg .pred p;\n mbarrier.try_wait.parity.shared::cta.b64 p, [%1], %2, %3;\n selp.u32 %0, 1, 0, p;\n}"
                     : "=r"(ok) : "r"(bar), "r"(par), "r"(10000) : "memory");
        if (ok) break;
        if (++it > SPIN_LIMIT) __trap();
    }
}
__device__ __forceinline__ void mbar_spin(uint32_t bar, uint32_t par) {
    uint32_t ok, it = 0;
    while (true) {
        asm volatile("{\n .reg .pred p;\n mbarrier.try_wait.parity.shared::cta.b64 p, [%1], %2;\n selp.u32 %0, 1, 0, p;\n}"
                     : "=r"(ok) : "r"(bar), "r"(par) : "memory");
        if (ok) break;
        if (++it > 16 * SPIN_LIMIT) __trap();
    }
}
__device__ __forceinline__ void tma_tile(uint32_t dst, const CUtensorMap* tm, int row, int half, uint32_t bar) {
    asm volatile("cp.async.bulk.tensor.3d.shared::cluster.global.mbarrier::complete_tx::bytes.L2::cache_hint [%0], [%1, {%3, %4, %5}], [%2], %6;"
                 :: "r"(dst), "l"(tm), "r"(bar), "r"(0), "r"(row), "r"(half), "l"(0x12F0000000000000ull) : "memory");
}
__device__ __forceinline__ void ldsm4(uint32_t addr, uint32_t* r) {
    asm volatile("ldmatrix.sync.aligned.m8n8.x4.shared.b16 {%0,%1,%2,%3}, [%4];"
                 : "=r"(r[0]), "=r"(r[1]), "=r"(r[2]), "=r"(r[3]) : "r"(addr) : "memory");
}
__device__ __forceinline__ void ldsm4t(uint32_t addr, uint32_t* r) {
    asm volatile("ldmatrix.sync.aligned.m8n8.x4.trans.shared.b16 {%0,%1,%2,%3}, [%4];"
                 : "=r"(r[0]), "=r"(r[1]), "=r"(r[2]), "=r"(r[3]) : "r"(addr) : "memory");
}
__device__ __forceinline__ void mma16816(float (&c)[4], uint32_t a0, uint32_t a1, uint32_t a2, uint32_t a3,
                                         uint32_t b0, uint32_t b1) {
    asm volatile("mma.sync.aligned.m16n8k16.row.col.f32.bf16.bf16.f32 {%0,%1,%2,%3}, {%4,%5,%6,%7}, {%8,%9}, {%0,%1,%2,%3};"
                 : "+f"(c[0]), "+f"(c[1]), "+f"(c[2]), "+f"(c[3])
                 : "r"(a0), "r"(a1), "r"(a2), "r"(a3), "r"(b0), "r"(b1));
}
__device__ __forceinline__ void bar_sync(int id, int n) { asm volatile("bar.sync %0, %1;" :: "r"(id), "r"(n) : "memory"); }
__device__ __forceinline__ void bar_arrive(int id, int n) { asm volatile("bar.arrive %0, %1;" :: "r"(id), "r"(n) : "memory"); }
__device__ __forceinline__ unsigned gtime32() { unsigned t; asm volatile("mov.u32 %0, %%globaltimer_lo;" : "=r"(t)); return t; }
__device__ __forceinline__ unsigned clock32() { unsigned t; asm volatile("mov.u32 %0, %%clock;" : "=r"(t)); return t; }
__device__ __forceinline__ void delay(unsigned clocks) { const unsigned c0 = clock32(); while (clock32() - c0 < clocks) {} }

__device__ __forceinline__ float bf16r(float v) {
    uint32_t d; asm("cvt.rn.bf16x2.f32 %0, %1, %2;" : "=r"(d) : "f"(v), "f"(0.f));
    return __uint_as_float(d);
}
__device__ __forceinline__ uint32_t pack_bf16(float lo, float hi) {
    uint32_t d; asm("cvt.rn.bf16x2.f32 %0, %1, %2;" : "=r"(d) : "f"(hi), "f"(lo));
    return d;
}
__device__ __forceinline__ float bf_lo(uint32_t u) { return __uint_as_float(u << 16); }
__device__ __forceinline__ float bf_hi(uint32_t u) { return __uint_as_float(u & 0xffff0000u); }
__device__ __forceinline__ float ex2(float v) { float r; asm("ex2.approx.ftz.f32 %0, %1;" : "=f"(r) : "f"(v)); return r; }
__device__ __forceinline__ float asf(uint32_t u) { return __uint_as_float(u); }

__device__ __forceinline__ uint32_t tagged(float v, uint32_t tag) { return (__float_as_uint(v) & ~3u) | tag; }
__device__ __forceinline__ void st1(float* p, uint32_t u) {
    asm volatile("st.relaxed.gpu.global.u32 [%0], %1;" :: "l"(p), "r"(u) : "memory");
}
__device__ __forceinline__ void st2(float* p, uint32_t u0, uint32_t u1) {
    asm volatile("st.relaxed.gpu.global.v2.u32 [%0], {%1, %2};" :: "l"(p), "r"(u0), "r"(u1) : "memory");
}
__device__ __forceinline__ float* other(float* p) { return reinterpret_cast<float*>(reinterpret_cast<uintptr_t>(p) ^ 4096u); }
__device__ __forceinline__ float4 cell_add(float* cell, float s, float f) {
    float4 p;
    asm volatile("atom.relaxed.gpu.global.add.v4.f32 {%0,%1,%2,%3}, [%4], {%5,%6,%7,%5};"
                 : "=f"(p.x), "=f"(p.y), "=f"(p.z), "=f"(p.w) : "l"(cell), "f"(1.f), "f"(s), "f"(f) : "memory");
    return p;
}
__device__ __forceinline__ uint4 ld4(const float* p) {
    uint4 v;
    asm volatile("ld.relaxed.gpu.global.v4.u32 {%0,%1,%2,%3}, [%4];" : "=r"(v.x), "=r"(v.y), "=r"(v.z), "=r"(v.w) : "l"(p) : "memory");
    return v;
}
__device__ __forceinline__ uint32_t badbits(const uint4& v, uint32_t tag) {
    uint32_t a, b;
    asm("lop3.b32 %0, %1, %2, %3, 0x7e;" : "=r"(a) : "r"(v.x), "r"(tag), "r"(v.y));
    asm("lop3.b32 %0, %1, %2, %3, 0x7e;" : "=r"(b) : "r"(v.z), "r"(tag), "r"(v.w));
    return a | b;
}
__device__ __forceinline__ void gather4(uint4 (&v)[4], const float* p0, const float* p1, const float* p2, const float* p3, uint32_t tag) {
    v[0] = ld4(p0); v[1] = ld4(p1); v[2] = ld4(p2); v[3] = ld4(p3);
    unsigned it = 0;
    while (true) {
        const uint32_t b0 = badbits(v[0], tag), b1 = badbits(v[1], tag), b2 = badbits(v[2], tag), b3 = badbits(v[3], tag);
        if (!__any_sync(0xffffffffu, ((b0 | b1) | (b2 | b3)) & 3u)) break;
        if (b0 & 3u) v[0] = ld4(p0);
        if (b1 & 3u) v[1] = ld4(p1);
        if (b2 & 3u) v[2] = ld4(p2);
        if (b3 & 3u) v[3] = ld4(p3);
        if (++it > SPIN_LIMIT) __trap();
    }
}
__device__ __forceinline__ float4 sum4(const uint4 (&v)[4]) {
    return make_float4((asf(v[0].x) + asf(v[1].x)) + (asf(v[2].x) + asf(v[3].x)), (asf(v[0].y) + asf(v[1].y)) + (asf(v[2].y) + asf(v[3].y)),
                       (asf(v[0].z) + asf(v[1].z)) + (asf(v[2].z) + asf(v[3].z)), (asf(v[0].w) + asf(v[1].w)) + (asf(v[2].w) + asf(v[3].w)));
}
__device__ __forceinline__ uint32_t near_side(volatile uint32_t* misc) {
    const uint32_t m0 = min(min(misc[40], misc[42]), min(misc[44], misc[46]));
    const uint32_t m1 = min(min(misc[41], misc[43]), min(misc[45], misc[47]));
    return m1 < m0;
}

__device__ __forceinline__ float gate(float f) {
    const float fr = bf16r(f);
    return bf16r(__fdividef(fr, 1.f + ex2(fr * -1.4426950408889634f)));
}
__device__ __forceinline__ __nv_bfloat16 finish(float x, float s, float g) { return __float2bfloat16_rn(x + bf16r(bf16r(s) * g)); }
__device__ __noinline__ float cell_redo(float* cell, float base, float a, float b) {
    for (unsigned it = 0; it < SPIN_LIMIT; it++) {
        const float c = asf(ld4(cell).x);
        if (c >= base && c < base + 32.f) return cell_add(cell, a, b).x;
    }
    __trap();
    return 0.f;
}
__device__ __noinline__ float2 cell_wait(const float* cell, float full) {
    for (unsigned it = 0; it < SPIN_LIMIT; it++) {
        const uint4 v = ld4(cell);
        if (asf(v.x) == full && asf(v.w) == full) return make_float2(asf(v.y), asf(v.z));
    }
    __trap();
    return make_float2(0.f, 0.f);
}

struct Ring {
    uint32_t full, empty;
    int slot; uint32_t phase;
    __device__ __forceinline__ void wait() { mbar_wait(full + slot * 8, phase); }
    __device__ __forceinline__ void next() { if (++slot == NSLOT) { slot = 0; phase ^= 1; } }
    __device__ __forceinline__ void release(int lane) {
        __syncwarp();
        if (lane == 0) mbar_arrive(empty + slot * 8);
        next();
    }
};

__global__ void __launch_bounds__(NTHREADS, 1)
fused_decode_kernel(const __grid_constant__ Params prm) {
    extern __shared__ uint8_t smem_raw[];
    const uint32_t sbase = ((uint32_t)__cvta_generic_to_shared(smem_raw) + 1023u) & ~1023u;
    uint8_t* sgen = smem_raw + (sbase - (uint32_t)__cvta_generic_to_shared(smem_raw));
    const int cta = blockIdx.x;
    const int hkv = cta >> 4, rhi = (cta >> 2) & 3, rlo = cta & 3;
    const bool has_w1 = cta < NFFN;
    const uint32_t bar_full = sbase + SM_BAR, bar_empty = bar_full + NSLOT * 8, bar_half = bar_empty + NSLOT * 8;

    if (threadIdx.x == 161) asm volatile("prefetch.global.L2 [%0];" :: "l"(prm.raw[3] + rhi * (128 * 8192) + (hkv * 4 + rlo) * 256));
    if (threadIdx.x - 1u < 31u) return;
    if (threadIdx.x == 0) {
        const unsigned t0 = gtime32();
        mbar_init(bar_full, 1);
        asm volatile("fence.mbarrier_init.release.cluster;" ::: "memory");
        mbar_expect_tx(bar_full, TILE_B);
        tma_tile(sbase, &prm.m[0], rhi * 128, (hkv * 4 + rlo) * 2, bar_full);
#pragma unroll
        for (int i = 1; i < 2 * NSLOT + 2; i++) mbar_init(bar_full + i * 8, (i < NSLOT || i >= 2 * NSLOT) ? 1 : 8);
        asm volatile("fence.mbarrier_init.release.cluster;" ::: "memory");
        volatile uint32_t* prole = reinterpret_cast<volatile uint32_t*>(sgen + SM_MISC) + 34;
        *prole = 0xffffffffu;
        asm volatile("barrier.arrive %0, %1;" :: "n"(BAR_XN), "n"(448) : "memory");
        const int kvrow = (rhi * 8 + hkv) * 16384 + 12288 + rlo * 64;
        const int toff = ((phase_key(cta) >> 2) * TAU) / 32 - (LEAD * TAU) / 16;
        constexpr int P_W1 = 18 + W1POS, P_W2 = 35, P_END = 38;
        int slot = 1; uint32_t eph = 1;
        int issued = 1;
        uint32_t role = 0;
#pragma unroll 1
        for (int v = 1; v < P_END; v++) {
            if (v == 31) {
                unsigned it = 0;
                while ((role = *prole) == 0xffffffffu) { if (++it > 16 * SPIN_LIMIT) __trap(); }
            }
            const int rh = role & 31, rc = role >> 5;
            const bool has_w2 = rh < 28;
            int mi, row, half;
            if (v == 1)          { mi = 0; row = rhi * 128 + 64; half = (hkv * 4 + rlo) * 2; }
            else if (v == P_W1)  { mi = 1; row = ((cta >> 1) & 7) * 64; half = (hkv * 2 + (cta & 1)) * 2; }
            else if (v < P_W2)   { const int j = v - 2 - (v > P_W1); mi = 2 + (j >> 4); row = kvrow + (j & 15) * 256; half = 0; }
            else if (v == P_W2)  { mi = 4; row = rh * 64; half = rc * 2; }
            else                 { mi = 5; row = rh * 128 + (v - P_W2 - 1) * 64; half = rc * 2; }
            if (v < 6) asm volatile("prefetch.tensormap [%0];" :: "l"(&prm.m[v]) : "memory");
            if (v == 10) asm volatile("cp.async.bulk.prefetch.L2.global [%0], 128;" :: "l"(prm.raw[0] + (size_t)kvrow * 256) : "memory");
            if (v == 31) {
                if (has_w2) asm volatile("cp.async.bulk.prefetch.L2.global [%0], 128;" :: "l"(prm.raw[1] + rh * 65536 + rc * 256) : "memory");
                asm volatile("cp.async.bulk.prefetch.L2.global [%0], 128;" :: "l"(prm.raw[2] + rh * 131072 + rc * 256) : "memory");
            }
            if ((v == P_W1 && !has_w1) || (v == P_W2 && !has_w2)) continue;
            if (issued >= INFLIGHT) {
                const int sc = slot - INFLIGHT;
                mbar_wait(bar_full + (sc < 0 ? sc + NSLOT : sc) * 8, sc < 0 ? eph : eph ^ 1);
            }
            if (issued >= NSLOT) mbar_wait(bar_empty + slot * 8, eph);
            {
                const int due = (v - (!has_w2 && v > P_W2)) * TAU + toff;
                int s2 = slot - 2; uint32_t par = eph ^ 1;
                if (s2 < 0) { s2 += NSLOT; par ^= 1; }
                while ((int)(gtime32() - t0) < due) {
                    if (v > 4 && mbar_test(bar_full + s2 * 8, par)) break;
                }
            }
            const uint32_t dst = sbase + slot * TILE_B, bf = bar_full + slot * 8;
            if (v > P_W2) {
                const uint32_t bh = bar_half + (v - P_W2 - 1) * 8;
                mbar_expect_tx(bf, TILE_B / 2);
                tma_tile(dst, &prm.m[5], row, half, bf);
                mbar_expect_tx(bh, TILE_B / 2);
                tma_tile(dst + TILE_B / 2, &prm.m[5], row + 32, half, bh);
            } else {
                mbar_expect_tx(bf, TILE_B);
                tma_tile(dst, &prm.m[mi], row, half, bf);
            }
            if (++slot == NSLOT) { slot = 0; eph ^= 1; }
            issued++;
        }
    }
    int tix;
    asm volatile("mov.u32 %0, %%tid.x;" : "=r"(tix));
    if (tix == 0) return;
    const int lane = tix & 31;
    const int wix = __shfl_sync(0xffffffffu, tix >> 5, 0);
    volatile uint32_t* misc = reinterpret_cast<volatile uint32_t*>(sgen + SM_MISC);

    if (wix < 5) {
        const int gw = wix - 1;
        {
            const uint4* xr = reinterpret_cast<const uint4*>(prm.x + gw * 512);
            const uint4 u0 = __ldg(xr + lane), u1 = __ldg(xr + 32 + lane);
            const uint32_t w[8] = {u0.x, u0.y, u0.z, u0.w, u1.x, u1.y, u1.z, u1.w};
            float s = 0.f;
#pragma unroll
            for (int i = 0; i < 8; i++) s += bf_lo(w[i]) + bf_hi(w[i]);
#pragma unroll
            for (int o = 16; o; o >>= 1) s += __shfl_xor_sync(0xffffffffu, s, o);
            const float mean = s * (1.f / 512.f);
            float vs = 0.f;
#pragma unroll
            for (int i = 0; i < 8; i++) { const float d0 = bf_lo(w[i]) - mean, d1 = bf_hi(w[i]) - mean; vs += d0 * d0 + d1 * d1; }
#pragma unroll
            for (int o = 16; o; o >>= 1) vs += __shfl_xor_sync(0xffffffffu, vs, o);
            const float mb = bf16r(mean);
            float den, rden;
            asm("sqrt.approx.f32 %0, %1;" : "=f"(den) : "f"(bf16r(bf16r(vs * (1.f / 512.f)) + 1e-5f)));
            asm("rcp.approx.f32 %0, %1;" : "=f"(rden) : "f"(bf16r(den)));
            uint32_t r[8];
#pragma unroll
            for (int i = 0; i < 8; i++) r[i] = pack_bf16(bf16r(bf_lo(w[i]) - mb) * rden, bf16r(bf_hi(w[i]) - mb) * rden);
            uint8_t* xs = sgen + SM_ACT + gw * ACT_PITCH + SEG_XN + lane * 16;
            *reinterpret_cast<uint4*>(xs) = make_uint4(r[0], r[1], r[2], r[3]);
            *reinterpret_cast<uint4*>(xs + 512) = make_uint4(r[4], r[5], r[6], r[7]);
        }
        bar_arrive(BAR_XN, 448);
        float wv[4] = {1.f, 1.f, 1.f, 1.f};
        const float* pa = prm.arena + AR_Q + (hkv * 16 + gw * 4) * 512 + rhi * 128 + lane * 4;
        const float* pb = pa + 1024;
#pragma unroll 1
        for (int r = 0; r < 2; r++) {
            bar_sync(r ? BAR_VGO : BAR_QGO, 384);
            const uint32_t tag = misc[32];
            if (r == 0) mbar_wait(bar_full + QSLOT * 8, 0);
            {
                uint4 v[4];
                gather4(v, pa, pa + 512, pb, pb + 512, tag);
                const float o0 = fmaf(wv[0], asf(v[0].x), wv[1] * asf(v[1].x)) + fmaf(wv[2], asf(v[2].x), wv[3] * asf(v[3].x));
                const float o1 = fmaf(wv[0], asf(v[0].y), wv[1] * asf(v[1].y)) + fmaf(wv[2], asf(v[2].y), wv[3] * asf(v[3].y));
                const float o2 = fmaf(wv[0], asf(v[0].z), wv[1] * asf(v[1].z)) + fmaf(wv[2], asf(v[2].z), wv[3] * asf(v[3].z));
                const float o3 = fmaf(wv[0], asf(v[0].w), wv[1] * asf(v[1].w)) + fmaf(wv[2], asf(v[2].w), wv[3] * asf(v[3].w));
                *reinterpret_cast<uint2*>(sgen + SM_ACT + gw * ACT_PITCH + (r ? SEG_O : SEG_Q) + lane * 8) =
                    make_uint2(pack_bf16(o0, o1), pack_bf16(o2, o3));
                bar_arrive(r ? BAR_O : BAR_Q, 384);
            }
            if (r) break;
            bar_sync(BAR_SGO, N_SGO);
            const int rh = misc[34] & 31;
            {
                const uint32_t side = near_side(misc);
                const int o = AR_O + slot_off((rh >> 2) * 16 + gw * 4) + (rh & 3) * 128 + lane * 4;
                pa = prm.arena + pick(o, side);
                pb = prm.arena + pick(o + 2048, side);
            }
            if (rh < 28) {
                const int rg = rh;
                const float* ph = prm.arena + AR_H + ((rg >> 1) * 8 + (lane >> 4) * 4) * 512 + gw * 128 + (rg & 1) * 64 + (lane & 15) * 4;
                uint4 v[4];
                gather4(v, ph, ph + 512, ph + 1024, ph + 1536, tag);
                float4 h = sum4(v);
                h.x += __shfl_xor_sync(0xffffffffu, h.x, 16); h.y += __shfl_xor_sync(0xffffffffu, h.y, 16);
                h.z += __shfl_xor_sync(0xffffffffu, h.z, 16); h.w += __shfl_xor_sync(0xffffffffu, h.w, 16);
                if (lane < 16)
                    *reinterpret_cast<uint2*>(sgen + SM_ACT + gw * ACT_PITCH + SEG_H + lane * 8) =
                        make_uint2(pack_bf16(fmaxf(h.x, 0.f), fmaxf(h.y, 0.f)), pack_bf16(fmaxf(h.z, 0.f), fmaxf(h.w, 0.f)));
                bar_arrive(BAR_H, 384);
            }
            {
                const float* ps = prm.arena + AR_XS + ((rh >> 2) * 16 + gw * 4 + (lane & 3)) * 8 + (rh & 2) * 2;
                uint4 v = ld4(ps);
                unsigned it = 0;
                while (__any_sync(0xffffffffu, badbits(v, tag) & 3u)) { v = ld4(ps); if (++it > SPIN_LIMIT) __trap(); }
                const float m = bf_hi((rh & 1) ? v.z : v.x);
                const float l = asf((rh & 1) ? v.w : v.y);
                float M = fmaxf(m, __shfl_xor_sync(0xffffffffu, m, 1));
                M = fmaxf(M, __shfl_xor_sync(0xffffffffu, M, 2));
                const float e = ex2((m - M) * 1.4426950408889634f);
                float L = e * l;
                L += __shfl_xor_sync(0xffffffffu, L, 1);
                L += __shfl_xor_sync(0xffffffffu, L, 2);
                const float wgt = __fdividef(e, L);
#pragma unroll
                for (int i = 0; i < 4; i++) wv[i] = __shfl_sync(0xffffffffu, wgt, i);
            }
        }
        return;
    }

    if (wix == 5) {
        if (lane == 0) {
            unsigned epoch;
            asm volatile("ld.relaxed.gpu.global.u32 %0, [%1];" : "=r"(epoch) : "l"(prm.arena + AR_EPOCH) : "memory");
            misc[32] = epoch + 1;
        }
        __syncwarp();
        bar_arrive(BAR_XN, 448);
        bar_sync(BAR_RGO, 288);
        const uint32_t tg = misc[32];
        const float* pw = prm.arena + AR_XS + lane * 8;
        uint4 sw[4];
        gather4(sw, pw, pw + 256, pw + 512, pw + 768, tg);
        uint32_t n1 = 0, below = 0;
#pragma unroll
        for (int i = 0; i < 4; i++) {
            const uint32_t ones = __ballot_sync(0xffffffffu, sw[i].x & 4u);
            n1 += __popc(ones);
            below += __popc(ones & __ballot_sync(0xffffffffu, phase_key(i * 32 + lane) < phase_key(cta)));
        }
        if (lane == 0) {
            const uint32_t rank = near_side(misc) ? NCTA - n1 + below : phase_key(cta) - below;
            misc[34] = ((rank >> 6) * 2 + (rank & 1)) * 32 + ((rank & 63) >> 1);
            if (cta == 0) *reinterpret_cast<unsigned*>(prm.arena + AR_EPOCH) = (tg == 3) ? 0u : tg;
        }
        bar_arrive(BAR_SGO, N_SGO);
        return;
    }

    const int warp = wix - 6;
    const int qslot = hkv * 16 + rlo * 4 + rhi, hslot = (hkv * 2 + (cta & 1)) * 8 + ((cta >> 1) & 7);
    {
        float* pr = prm.arena + pick(AR_O + slot_off(cta) + (warp >> 1) * 128, warp & 1);
        if (lane < 4) st2(pr + lane * 2, 0u, 0u);
        bar_sync(BAR_MMA, 256);
        delay(200);
        if (lane == 0) {
            uint32_t v, c1;
            const uint32_t c0 = clock32();
            asm volatile("atom.relaxed.gpu.global.add.u32 %0, [%1], 4;" : "=r"(v) : "l"(pr) : "memory");
            asm volatile("{\n .reg .pred p;\n setp.ne.u32 p, %1, 1;\n mov.u32 %0, 0;\n @p mov.u32 %0, %%clock;\n}" : "=r"(c1) : "r"(v));
            misc[40 + warp] = c1 - c0;
        }
        __syncwarp();
    }
    const int g = lane >> 2, t = lane & 3;
    Ring ring{bar_full, bar_empty, 0, 0u};
    const int lrow = lane & 7, lmat = lane >> 3;
    const uint32_t a_lane = (lrow + ((lmat >> 1) << 3)) * 128 + ((((warp & 3) * 2 + (lmat & 1)) ^ lrow) << 4);
    const uint32_t a_off = sbase + (warp >> 2) * 8192 + a_lane;
    const uint32_t b_off = sbase + SM_ACT + (lane & 3) * ACT_PITCH + lmat * 16;
    const bool hi = t >= 2;
    const int pofs = (t & 1) * 256 + warp * 16 + g + (t >> 1) * 8;
    float* const myslot = prm.arena + slot_off(cta);
    float* cell = nullptr;
    bool has_w2 = false;
    float f0 = 0.f, f1 = 0.f, x0 = 0.f, x1 = 0.f;
    float4 pf = make_float4(0.f, 0.f, 0.f, 0.f);
    float* cell1 = nullptr;
    int oidx = 0;
    bar_sync(BAR_XN, 448);
    const uint32_t tag = misc[32];

    float vs[4] = {0.f, 0.f, 0.f, 0.f};
#pragma unroll 1
    for (int sg = 0; sg < 5; sg++) {
        if (sg == 1) {
            if (warp == 0 && lane < 4) st2(prm.arena + AR_XS + cta * 8 + lane * 2, 0u, 0u);
            if (warp == 1 && lane < 16) {
                const uint32_t base = __float_as_uint(128.f * tag);
                asm volatile("st.relaxed.gpu.global.v4.u32 [%0], {%1,%2,%2,%1};"
                             :: "l"(prm.arena + pick(AR_C + (cta >> 4) * 2048, cta >> 6) + (cta & 15) * 64 + lane * 4), "r"(base), "r"(0u) : "memory");
            }
            bar_sync(BAR_Q, 384);
            uint32_t qa[16];
            const uint8_t* qs = sgen + SM_ACT + (g & 3) * ACT_PITCH + SEG_Q + t * 4;
#pragma unroll
            for (int k = 0; k < 16; k++) qa[k] = *reinterpret_cast<const uint32_t*>(qs + k * 16);
            const uint32_t k_off = sbase + (warp * 8 + lrow) * 128;
            const uint32_t sw0 = (lmat ^ lrow) << 4, sw1 = ((lmat + 4) ^ lrow) << 4;
            float mx = -INFINITY;
            uint8_t* sdst = sgen + SM_ACT + g * ACT_PITCH + SEG_P + (warp * 8 + 2 * t) * 2;
#pragma unroll 1
            for (int it = 0; it < KT; it++) {
                ring.wait();
                const uint32_t tb = ring.slot * TILE_B + k_off;
                uint32_t b[16];
                ldsm4(tb + sw0, b); ldsm4(tb + sw1, b + 4); ldsm4(tb + 8192 + sw0, b + 8); ldsm4(tb + 8192 + sw1, b + 12);
                float c0[4] = {0.f, 0.f, 0.f, 0.f}, c1[4] = {0.f, 0.f, 0.f, 0.f};
#pragma unroll
                for (int k = 0; k < 8; k += 2) {
                    mma16816(c0, qa[2 * k], 0u, qa[2 * k + 1], 0u, b[2 * k], b[2 * k + 1]);
                    mma16816(c1, qa[2 * k + 2], 0u, qa[2 * k + 3], 0u, b[2 * k + 2], b[2 * k + 3]);
                }
                ring.release(lane);
                const float scale = 0.08838834764831845f;
                const uint32_t sp = pack_bf16(bf16r(c0[0] + c1[0]) * scale, bf16r(c0[1] + c1[1]) * scale);
                mx = fmaxf(mx, fmaxf(bf_lo(sp), bf_hi(sp)));
                if (lane < 16) *reinterpret_cast<uint32_t*>(sdst + it * 128) = sp;
            }
            mx = fmaxf(mx, __shfl_xor_sync(0xffffffffu, mx, 1));
            mx = fmaxf(mx, __shfl_xor_sync(0xffffffffu, mx, 2));
            if (lane < 16 && t == 0) reinterpret_cast<float*>(sgen + SM_WMAX)[warp * 4 + g] = mx;
            bar_sync(BAR_MMA, 256);
            const int head = warp >> 1;
            const float* wm = reinterpret_cast<const float*>(sgen + SM_WMAX) + head;
            float m = wm[0];
#pragma unroll
            for (int i = 1; i < 8; i++) m = fmaxf(m, wm[4 * i]);
            uint8_t* pp = sgen + SM_ACT + head * ACT_PITCH + SEG_P + (warp & 1) * 1024 + lane * 16;
            float l = 0.f;
#pragma unroll 1
            for (int h = 0; h < 2; h++) {
                const uint4 u = *reinterpret_cast<const uint4*>(pp + h * 512);
                uint32_t w[4] = {u.x, u.y, u.z, u.w};
#pragma unroll
                for (int i = 0; i < 4; i++) {
                    const float L2E = 1.4426950408889634f;
                    const float p0 = ex2((bf_lo(w[i]) - m) * L2E), p1 = ex2((bf_hi(w[i]) - m) * L2E);
                    l += p0 + p1;
                    w[i] = pack_bf16(p0, p1);
                }
                *reinterpret_cast<uint4*>(pp + h * 512) = make_uint4(w[0], w[1], w[2], w[3]);
            }
#pragma unroll
            for (int o = 16; o; o >>= 1) l += __shfl_xor_sync(0xffffffffu, l, o);
            if (lane == 0) reinterpret_cast<float*>(sgen + SM_LSUM)[warp] = l;
            bar_sync(BAR_MMA, 256);
            if ((warp & 1) && lane < 2) {
                const float* ls = reinterpret_cast<const float*>(sgen + SM_LSUM);
                st1(prm.arena + AR_XS + cta * 8 + head * 2 + lane, lane ? tagged(ls[warp - 1] + ls[warp], tag) : (__float_as_uint(m) | tag | (near_side(misc) << 2)));
            }
        }
        if ((sg == 2 && !has_w1) || (sg == 4 && !has_w2)) continue;
        const int i0 = (sg == 3) ? W1POS : (sg == 1) ? 0 : 32;
        const int i1 = (sg == 3) ? KT : (sg == 1) ? W1POS : (sg == 0) ? 34 : 33;
        const int seg = (sg == 0) ? SEG_XN + rhi * 256 : (sg == 2) ? SEG_XN + ((cta >> 1) & 7) * 128 : (sg == 4) ? SEG_H : SEG_P + i0 * 128;
        float* const pd = (sg == 0 ? prm.arena + AR_Q + qslot * 512 : sg == 2 ? prm.arena + AR_H + hslot * 512 : myslot + AR_O) + pofs;
        uint32_t ba = b_off + seg;
        float c0[4], c1[4];
#pragma unroll
        for (int k = 0; k < 4; k++) { c0[k] = sg == 3 ? vs[k] : 0.f; c1[k] = 0.f; }
        if (sg == 4) bar_sync(BAR_H, 384);
#pragma unroll 1
        for (int i = i0; i < i1; i++) {
            if (i == RGO) bar_arrive(BAR_RGO, 288);
            if (i == SGO) {
                bar_sync(BAR_SGO, N_SGO);
                const int role = misc[34], col = warp * 16 + g + (t >> 1) * 8;
                cell = prm.arena + pick(AR_C + (role >> 5) * 4096, role >> 6) + (col * 2 + (t & 1)) * 4;
                cell1 = other(cell) + 2048;
                oidx = (t & 1) * 1024 + (role >> 5) * 128 + col;
                has_w2 = (role & 31) < 28;
                x0 = __bfloat162float(prm.x[oidx]); x1 = __bfloat162float(prm.x[oidx + 512]);
            }
            if (i == CLRO) { st1(pd, 0u); st1(pd + 128, 0u); st1(pd + 1024, 0u); st1(pd + 1152, 0u); }
            uint32_t a[16], b[8];
            ldsm4(ba, b); ldsm4(ba + 64, b + 4);
            ring.wait();
            const uint32_t aa = a_off + ring.slot * TILE_B;
#pragma unroll
            for (int k = 0; k < 4; k++) ldsm4t(aa + k * 2048, a + 4 * k);
            mma16816(c0, a[0], a[1], a[2], a[3], b[0], b[1]);
            mma16816(c1, a[4], a[5], a[6], a[7], b[2], b[3]);
            mma16816(c0, a[8], a[9], a[10], a[11], b[4], b[5]);
            mma16816(c1, a[12], a[13], a[14], a[15], b[6], b[7]);
            ring.release(lane);
            ba += 128;
        }
        if (sg == 1) {
#pragma unroll
            for (int k = 0; k < 4; k++) vs[k] = c0[k] + c1[k];
            continue;
        }
        const float e0 = hi ? c0[2] + c1[2] : c0[0] + c1[0], e1 = hi ? c0[3] + c1[3] : c0[1] + c1[1];
        if (sg == 4) { f0 = e0; f1 = e1; pf = cell_add(cell1, e0, e1); }
        else {
            const uint32_t r0 = tagged(e0, tag), r1 = tagged(e1, tag);
            st1(pd, r0); st1(pd + 128, r1);
            if (sg == 3) { st1(pd + 1024, r0); st1(pd + 1152, r1); }
            if (sg != 2) bar_arrive(sg ? BAR_VGO : BAR_QGO, 384);
        }
    }
    {
        uint32_t a[8], b[16];
        float c[4][4];
#pragma unroll
        for (int k = 0; k < 4; k++) { c[k][0] = 0.f; c[k][1] = 0.f; c[k][2] = 0.f; c[k][3] = 0.f; }
        const uint32_t ap_off = sbase + (warp >> 2) * 4096 + a_lane;
        __nv_bfloat16* const optr = prm.out + oidx;
        uint4 fv;
        bar_sync(BAR_O, 384);
#pragma unroll
        for (int k = 0; k < 4; k++) ldsm4(b_off + SEG_O + k * 64, b + 4 * k);
#pragma unroll
        for (int q = 0; q < 4; q++) {
            const uint32_t bq = (q & 1) ? bar_half + (q >> 1) * 8 : ring.full + ring.slot * 8;
            const uint32_t pq = (q & 1) ? 0u : ring.phase;
            const uint32_t aa = ap_off + ring.slot * TILE_B + (q & 1) * (TILE_B / 2);
            if (q >= 2) mbar_spin(bq, pq); else mbar_wait(bq, pq);
            ldsm4t(aa, a); ldsm4t(aa + 2048, a + 4);
            if (q == 3) fv = ld4(cell1);
            mma16816(c[(2 * q) & 3], a[0], a[1], a[2], a[3], b[4 * q], b[4 * q + 1]);
            mma16816(c[(2 * q + 1) & 3], a[4], a[5], a[6], a[7], b[4 * q + 2], b[4 * q + 3]);
            if (q & 1) ring.next();
        }
        const float r0 = ((hi ? c[0][2] : c[0][0]) + (hi ? c[1][2] : c[1][0])) + ((hi ? c[2][2] : c[2][0]) + (hi ? c[3][2] : c[3][0]));
        const float r1 = ((hi ? c[0][3] : c[0][1]) + (hi ? c[1][3] : c[1][1])) + ((hi ? c[2][3] : c[2][1]) + (hi ? c[3][3] : c[3][1]));
        const float4 p = cell_add(cell, r0, r1);
        const float base = 128.f * tag;
        const float g0 = gate(asf(fv.y)), g1 = gate(asf(fv.z));
        const bool fok = asf(fv.x) == base + 28.f && asf(fv.w) == base + 28.f;
        const bool last = p.x == base + 31.f;
        if (last) { optr[0] = finish(x0, p.y + r0, g0); optr[512] = finish(x1, p.z + r1, g1); }
        const bool sin = fabsf(p.x - (base + 15.5f)) < 16.f, fin = !has_w2 || fabsf(pf.x - (base + 15.5f)) < 16.f;
        if (!(sin && fin) || (last && !(fok && p.w == p.x)) || (pf.w < 0.f && pf.y == pf.z)) {
            if (!fin) cell_redo(cell1, base, f0, f1);
            const float c = sin ? p.x : cell_redo(cell, base, r0, r1);
            if (c == base + 31.f) {
                const float2 sv = cell_wait(cell, base + 32.f), fw = cell_wait(cell1, base + 28.f);
                optr[0] = finish(x0, sv.x, gate(fw.x)); optr[512] = finish(x1, sv.y, gate(fw.y));
            }
        }
    }
}

typedef CUresult (*EncodeFn)(CUtensorMap*, CUtensorMapDataType, cuuint32_t, void*, const cuuint64_t*, const cuuint64_t*,
                             const cuuint32_t*, const cuuint32_t*, CUtensorMapInterleave, CUtensorMapSwizzle,
                             CUtensorMapL2promotion, CUtensorMapFloatOOBfill);

void make_map(EncodeFn enc, CUtensorMap* m, const void* base, uint64_t rows, uint64_t cols, uint32_t box_rows) {
    cuuint64_t dims[3] = {64, rows, cols / 64};
    cuuint64_t strides[2] = {cols * 2, 128};
    cuuint32_t box[3] = {64, box_rows, 2};
    cuuint32_t es[3] = {1, 1, 1};
    enc(m, CU_TENSOR_MAP_DATA_TYPE_BFLOAT16, 3, const_cast<void*>(base), dims, strides, box, es,
        CU_TENSOR_MAP_INTERLEAVE_NONE, CU_TENSOR_MAP_SWIZZLE_128B, CU_TENSOR_MAP_L2_PROMOTION_L2_256B,
        CU_TENSOR_MAP_FLOAT_OOB_FILL_NONE);
}

}

extern "C" void kernel_launch(void* const* d_in, const int* in_sizes, int n_in, void* d_out, int out_size) {
    (void)in_sizes; (void)n_in; (void)out_size;
    static EncodeFn enc = nullptr;
    static void* arena_ptr = nullptr;
    if (!enc) {
        void* fn = nullptr;
        cudaDriverEntryPointQueryResult qr;
        cudaGetDriverEntryPoint("cuTensorMapEncodeTiled", &fn, cudaEnableDefault, &qr);
        enc = (EncodeFn)fn;
        cudaGetSymbolAddress(&arena_ptr, g_arena);
        cudaFuncSetAttribute(fused_decode_kernel, cudaFuncAttributeMaxDynamicSharedMemorySize, SM_TOTAL + 1024);
    }
    Params prm;
    make_map(enc, &prm.m[0], d_in[3], 512, 4096, 64);
    make_map(enc, &prm.m[1], d_in[6], 512, 1792, 64);
    make_map(enc, &prm.m[2], d_in[1], 4ull * 8 * 16384, 128, 64);
    make_map(enc, &prm.m[3], d_in[2], 4ull * 8 * 16384, 128, 64);
    make_map(enc, &prm.m[4], d_in[7], 1792, 512, 64);
    make_map(enc, &prm.m[5], d_in[4], 4096, 512, 32);
    prm.raw[0] = (const char*)d_in[2];
    prm.raw[1] = (const char*)d_in[7];
    prm.raw[2] = (const char*)d_in[4];
    prm.raw[3] = (const char*)d_in[3];
    prm.x = (const __nv_bfloat16*)d_in[0];
    prm.out = (__nv_bfloat16*)d_out;
    prm.arena = (float*)(((uintptr_t)arena_ptr + 0x600000ull) & ~0x1fffffull);
    fused_decode_kernel<<<NCTA, NTHREADS, SM_TOTAL + 1024>>>(prm);
}
```

```cpp
#include <cuda_runtime.h>
#include <cuda_bf16.h>
#include <cuda.h>
#include <stdint.h>

namespace {

constexpr int NCTA     = 128;
constexpr int NFFN     = 112;
constexpr int NSLOT    = 13;
constexpr int TILE_B   = 16384;
constexpr int KT       = 16;
constexpr int NTHREADS = 448;

constexpr int TAU      = 655;
constexpr int LEAD     = 21;
constexpr int INFLIGHT = 8;
constexpr int W1POS    = 6;
constexpr int QSLOT = 5;
constexpr int RGO   = 4;
constexpr int SGO   = 10;
constexpr int CLRO  = 12;

constexpr int SEG_XN = 0;
constexpr int SEG_P  = 1024;
constexpr int SEG_H  = 3072;
constexpr int SEG_O  = 3200;
constexpr int SEG_Q  = 3456;
constexpr int ACT_PITCH = 3712 + 16;
constexpr int SM_ACT   = NSLOT * TILE_B;
constexpr int SM_WMAX  = SM_ACT + 4 * ACT_PITCH;
constexpr int SM_LSUM  = SM_WMAX + 128;
constexpr int SM_MISC  = SM_LSUM + 32;
constexpr int SM_BAR   = SM_MISC + 256;
constexpr int SM_TOTAL = SM_BAR + (2 * NSLOT + 2) * 8;
static_assert(SM_TOTAL + 1024 <= 232448, "smem");

constexpr int BAR_MMA = 1, BAR_XN = 2, BAR_Q = 3, BAR_H = 4, BAR_O = 5, BAR_VGO = 6, BAR_QGO = 7, BAR_SGO = 8,
              BAR_RGO = 9;
constexpr int N_SGO = 416;

__device__ __align__(4096) float g_arena[1 << 21];
constexpr int AR_O = 0, AR_C = 262144, AR_Q = 393216, AR_H = 458752;
constexpr int AR_XS = 258048;
constexpr int AR_EPOCH = AR_XS + 2048;
constexpr uint32_t HOME_MASK = (1u << 12) | (1u << 13) | (1u << 16) | (1u << 17) | (1u << 19);

struct Params {
    CUtensorMap m[6];
    const char* raw[4];
    const __nv_bfloat16* x;
    __nv_bfloat16* out;
    float* arena;
};

constexpr unsigned SPIN_LIMIT = 1u << 20;

__device__ __forceinline__ int phase_key(int cta) { return (((cta >> 2) * 13) & 31) * 4 + (cta & 3); }
__device__ __forceinline__ int slot_off(int producer) { return (producer >> 1) * 2048 + (producer & 1) * 512; }
__device__ __forceinline__ uint32_t parity(int off) { return __popc(((uint32_t)off << 2) & HOME_MASK) & 1u; }
__device__ __forceinline__ int pick(int off, uint32_t side) { return off + (int)((parity(off) ^ side) << 10); }

__device__ __forceinline__ void mbar_init(uint32_t bar, uint32_t cnt) {
    asm volatile("mbarrier.init.shared::cta.b64 [%0], %1;" :: "r"(bar), "r"(cnt) : "memory");
}
__device__ __forceinline__ void mbar_expect_tx(uint32_t bar, uint32_t bytes) {
    asm volatile("mbarrier.arrive.expect_tx.shared::cta.b64 _, [%0], %1;" :: "r"(bar), "r"(bytes) : "memory");
}
__device__ __forceinline__ void mbar_arrive(uint32_t bar) {
    asm volatile("mbarrier.arrive.shared::cta.b64 _, [%0];" :: "r"(bar) : "memory");
}
__device__ __forceinline__ bool mbar_test(uint32_t bar, uint32_t par) {
    uint32_t ok;
    asm volatile("{\n .reg .pred p;\n mbarrier.test_wait.parity.shared::cta.b64 p, [%1], %2;\n selp.u32 %0, 1, 0, p;\n}"
                 : "=r"(ok) : "r"(bar), "r"(par) : "memory");
    return ok;
}
__device__ __forceinline__ void mbar_wait(uint32_t bar, uint32_t par) {
    uint32_t ok, it = 0;
    while (true) {
        asm volatile("{\n .reg .pred p;\n mbarrier.try_wait.parity.shared::cta.b64 p, [%1], %2, %3;\n selp.u32 %0, 1, 0, p;\n}"
                     : "=r"(ok) : "r"(bar), "r"(par), "r"(10000) : "memory");
        if (ok) break;
        if (++it > SPIN_LIMIT) __trap();
    }
}
__device__ __forceinline__ void mbar_spin(uint32_t bar, uint32_t par) {
    uint32_t ok, it = 0;
    while (true) {
        asm volatile("{\n .reg .pred p;\n mbarrier.try_wait.parity.shared::cta.b64 p, [%1], %2;\n selp.u32 %0, 1, 0, p;\n}"
                     : "=r"(ok) : "r"(bar), "r"(par) : "memory");
        if (ok) break;
        if (++it > 16 * SPIN_LIMIT) __trap();
    }
}
__device__ __forceinline__ void tma_tile(uint32_t dst, const CUtensorMap* tm, int row, int half, uint32_t bar) {
    asm volatile("cp.async.bulk.tensor.3d.shared::cluster.global.mbarrier::complete_tx::bytes.L2::cache_hint [%0], [%1, {%3, %4, %5}], [%2], %6;"
                 :: "r"(dst), "l"(tm), "r"(bar), "r"(0), "r"(row), "r"(half), "l"(0x12F0000000000000ull) : "memory");
}
__device__ __forceinline__ void ldsm4(uint32_t addr, uint32_t* r) {
    asm volatile("ldmatrix.sync.aligned.m8n8.x4.shared.b16 {%0,%1,%2,%3}, [%4];"
                 : "=r"(r[0]), "=r"(r[1]), "=r"(r[2]), "=r"(r[3]) : "r"(addr) : "memory");
}
__device__ __forceinline__ void ldsm4t(uint32_t addr, uint32_t* r) {
    asm volatile("ldmatrix.sync.aligned.m8n8.x4.trans.shared.b16 {%0,%1,%2,%3}, [%4];"
                 : "=r"(r[0]), "=r"(r[1]), "=r"(r[2]), "=r"(r[3]) : "r"(addr) : "memory");
}
__device__ __forceinline__ void mma16816(float (&c)[4], uint32_t a0, uint32_t a1, uint32_t a2, uint32_t a3,
                                         uint32_t b0, uint32_t b1) {
    asm volatile("mma.sync.aligned.m16n8k16.row.col.f32.bf16.bf16.f32 {%0,%1,%2,%3}, {%4,%5,%6,%7}, {%8,%9}, {%0,%1,%2,%3};"
                 : "+f"(c[0]), "+f"(c[1]), "+f"(c[2]), "+f"(c[3])
                 : "r"(a0), "r"(a1), "r"(a2), "r"(a3), "r"(b0), "r"(b1));
}
__device__ __forceinline__ void bar_sync(int id, int n) { asm volatile("bar.sync %0, %1;" :: "r"(id), "r"(n) : "memory"); }
__device__ __forceinline__ void bar_arrive(int id, int n) { asm volatile("bar.arrive %0, %1;" :: "r"(id), "r"(n) : "memory"); }
__device__ __forceinline__ unsigned gtime32() { unsigned t; asm volatile("mov.u32 %0, %%globaltimer_lo;" : "=r"(t)); return t; }
__device__ __forceinline__ unsigned clock32() { unsigned t; asm volatile("mov.u32 %0, %%clock;" : "=r"(t)); return t; }
__device__ __forceinline__ void delay(unsigned clocks) { const unsigned c0 = clock32(); while (clock32() - c0 < clocks) {} }

__device__ __forceinline__ float bf16r(float v) {
    uint32_t d; asm("cvt.rn.bf16x2.f32 %0, %1, %2;" : "=r"(d) : "f"(v), "f"(0.f));
    return __uint_as_float(d);
}
__device__ __forceinline__ uint32_t pack_bf16(float lo, float hi) {
    uint32_t d; asm("cvt.rn.bf16x2.f32 %0, %1, %2;" : "=r"(d) : "f"(hi), "f"(lo));
    return d;
}
__device__ __forceinline__ float bf_lo(uint32_t u) { return __uint_as_float(u << 16); }
__device__ __forceinline__ float bf_hi(uint32_t u) { return __uint_as_float(u & 0xffff0000u); }
__device__ __forceinline__ float ex2(float v) { float r; asm("ex2.approx.ftz.f32 %0, %1;" : "=f"(r) : "f"(v)); return r; }
__device__ __forceinline__ float asf(uint32_t u) { return __uint_as_float(u); }

__device__ __forceinline__ uint32_t tagged(float v, uint32_t tag) { return (__float_as_uint(v) & ~3u) | tag; }
__device__ __forceinline__ void st1(float* p, uint32_t u) {
    asm volatile("st.relaxed.gpu.global.u32 [%0], %1;" :: "l"(p), "r"(u) : "memory");
}
__device__ __forceinline__ void st2(float* p, uint32_t u0, uint32_t u1) {
    asm volatile("st.relaxed.gpu.global.v2.u32 [%0], {%1, %2};" :: "l"(p), "r"(u0), "r"(u1) : "memory");
}
__device__ __forceinline__ float* other(float* p) { return reinterpret_cast<float*>(reinterpret_cast<uintptr_t>(p) ^ 4096u); }
__device__ __forceinline__ float4 cell_add(float* cell, float s, float f) {
    float4 p;
    asm volatile("atom.relaxed.gpu.global.add.v4.f32 {%0,%1,%2,%3}, [%4], {%5,%6,%7,%5};"
                 : "=f"(p.x), "=f"(p.y), "=f"(p.z), "=f"(p.w) : "l"(cell), "f"(1.f), "f"(s), "f"(f) : "memory");
    return p;
}
__device__ __forceinline__ uint4 ld4(const float* p) {
    uint4 v;
    asm volatile("ld.relaxed.gpu.global.v4.u32 {%0,%1,%2,%3}, [%4];" : "=r"(v.x), "=r"(v.y), "=r"(v.z), "=r"(v.w) : "l"(p) : "memory");
    return v;
}
__device__ __forceinline__ uint32_t badbits(const uint4& v, uint32_t tag) {
    uint32_t a, b;
    asm("lop3.b32 %0, %1, %2, %3, 0x7e;" : "=r"(a) : "r"(v.x), "r"(tag), "r"(v.y));
    asm("lop3.b32 %0, %1, %2, %3, 0x7e;" : "=r"(b) : "r"(v.z), "r"(tag), "r"(v.w));
    return a | b;
}
__device__ __forceinline__ void gather4(uint4 (&v)[4], const float* p0, const float* p1, const float* p2, const float* p3, uint32_t tag) {
    v[0] = ld4(p0); v[1] = ld4(p1); v[2] = ld4(p2); v[3] = ld4(p3);
    unsigned it = 0;
    while (true) {
        const uint32_t b0 = badbits(v[0], tag), b1 = badbits(v[1], tag), b2 = badbits(v[2], tag), b3 = badbits(v[3], tag);
        if (!__any_sync(0xffffffffu, ((b0 | b1) | (b2 | b3)) & 3u)) break;
        if (b0 & 3u) v[0] = ld4(p0);
        if (b1 & 3u) v[1] = ld4(p1);
        if (b2 & 3u) v[2] = ld4(p2);
        if (b3 & 3u) v[3] = ld4(p3);
        if (++it > SPIN_LIMIT) __trap();
    }
}
__device__ __forceinline__ float4 sum4(const uint4 (&v)[4]) {
    return make_float4((asf(v[0].x) + asf(v[1].x)) + (asf(v[2].x) + asf(v[3].x)), (asf(v[0].y) + asf(v[1].y)) + (asf(v[2].y) + asf(v[3].y)),
                       (asf(v[0].z) + asf(v[1].z)) + (asf(v[2].z) + asf(v[3].z)), (asf(v[0].w) + asf(v[1].w)) + (asf(v[2].w) + asf(v[3].w)));
}
__device__ __forceinline__ uint32_t near_side(volatile uint32_t* misc) {
    const uint32_t m0 = min(min(misc[40], misc[42]), min(misc[44], misc[46]));
    const uint32_t m1 = min(min(misc[41], misc[43]), min(misc[45], misc[47]));
    return m1 < m0;
}

__device__ __forceinline__ float gate(float f) {
    const float fr = bf16r(f);
    return bf16r(__fdividef(fr, 1.f + ex2(fr * -1.4426950408889634f)));
}
__device__ __forceinline__ __nv_bfloat16 finish(float x, float s, float g) { return __float2bfloat16_rn(x + bf16r(bf16r(s) * g)); }
__device__ __noinline__ float cell_redo(float* cell, float base, float a, float b) {
    for (unsigned it = 0; it < SPIN_LIMIT; it++) {
        const float c = asf(ld4(cell).x);
        if (c >= base && c < base + 32.f) return cell_add(cell, a, b).x;
    }
    __trap();
    return 0.f;
}
__device__ __noinline__ float2 cell_wait(const float* cell, float full) {
    for (unsigned it = 0; it < SPIN_LIMIT; it++) {
        const uint4 v = ld4(cell);
        if (asf(v.x) == full && asf(v.w) == full) return make_float2(asf(v.y), asf(v.z));
    }
    __trap();
    return make_float2(0.f, 0.f);
}

struct Ring {
    uint32_t full, empty;
    int slot; uint32_t phase;
    __device__ __forceinline__ void wait() { mbar_wait(full + slot * 8, phase); }
    __device__ __forceinline__ void next() { if (++slot == NSLOT) { slot = 0; phase ^= 1; } }
    __device__ __forceinline__ void release(int lane) {
        __syncwarp();
        if (lane == 0) mbar_arrive(empty + slot * 8);
        next();
    }
};

__global__ void __launch_bounds__(NTHREADS, 1)
fused_decode_kernel(const __grid_constant__ Params prm) {
    extern __shared__ uint8_t smem_raw[];
    const uint32_t sbase = ((uint32_t)__cvta_generic_to_shared(smem_raw) + 1023u) & ~1023u;
    uint8_t* sgen = smem_raw + (sbase - (uint32_t)__cvta_generic_to_shared(smem_raw));
    const int cta = blockIdx.x;
    const int hkv = cta >> 4, rhi = (cta >> 2) & 3, rlo = cta & 3;
    const bool has_w1 = cta < NFFN;
    const uint32_t bar_full = sbase + SM_BAR, bar_empty = bar_full + NSLOT * 8, bar_half = bar_empty + NSLOT * 8;

    if (threadIdx.x == 161) asm volatile("prefetch.global.L2 [%0];" :: "l"(prm.raw[3] + rhi * (128 * 8192) + (hkv * 4 + rlo) * 256));
    if (threadIdx.x - 1u < 31u) return;
    if (threadIdx.x == 0) {
        const unsigned t0 = gtime32();
        mbar_init(bar_full, 1);
        asm volatile("fence.mbarrier_init.release.cluster;" ::: "memory");
        mbar_expect_tx(bar_full, TILE_B);
        tma_tile(sbase, &prm.m[0], rhi * 128, (hkv * 4 + rlo) * 2, bar_full);
#pragma unroll
        for (int i = 1; i < 2 * NSLOT + 2; i++) mbar_init(bar_full + i * 8, (i < NSLOT || i >= 2 * NSLOT) ? 1 : 8);
        asm volatile("fence.mbarrier_init.release.cluster;" ::: "memory");
        volatile uint32_t* prole = reinterpret_cast<volatile uint32_t*>(sgen + SM_MISC) + 34;
        *prole = 0xffffffffu;
        asm volatile("barrier.arrive %0, %1;" :: "n"(BAR_XN), "n"(448) : "memory");
        const int kvrow = (rhi * 8 + hkv) * 16384 + 12288 + (rlo & 1) * 64 + (rlo >> 1) * 256;
        const int toff = ((phase_key(cta) >> 2) * TAU) / 32 - (LEAD * TAU) / 16;
        constexpr int P_W1 = 18 + W1POS, P_W2 = 35, P_END = 38;
        int slot = 1; uint32_t eph = 1;
        int issued = 1;
        uint32_t role = 0;
#pragma unroll 1
        for (int v = 1; v < P_END; v++) {
            if (v == 31) {
                unsigned it = 0;
                while ((role = *prole) == 0xffffffffu) { if (++it > 16 * SPIN_LIMIT) __trap(); }
            }
            const int rh = role & 31, rc = role >> 5;
            const bool has_w2 = rh < 28;
            int mi, row, half;
            if (v == 1)          { mi = 0; row = rhi * 128 + 64; half = (hkv * 4 + rlo) * 2; }
            else if (v == P_W1)  { mi = 1; row = ((cta >> 1) & 7) * 64; half = (hkv * 2 + (cta & 1)) * 2; }
            else if (v < P_W2)   { const int j = v - 2 - (v > P_W1); mi = 2 + (j >> 4); row = kvrow + (j & 1) * 128 + ((j & 15) >> 1) * 512; half = 0; }
            else if (v == P_W2)  { mi = 4; row = rh * 64; half = rc * 2; }
            else                 { mi = 5; row = rh * 128 + (v - P_W2 - 1) * 32; half = rc * 2; }
            if (v < 6) asm volatile("prefetch.tensormap [%0];" :: "l"(&prm.m[v]) : "memory");
            if (v == 10) asm volatile("cp.async.bulk.prefetch.L2.global [%0], 128;" :: "l"(prm.raw[0] + (size_t)kvrow * 256) : "memory");
            if (v == 31) {
                if (has_w2) asm volatile("cp.async.bulk.prefetch.L2.global [%0], 128;" :: "l"(prm.raw[1] + rh * 65536 + rc * 256) : "memory");
                asm volatile("cp.async.bulk.prefetch.L2.global [%0], 128;" :: "l"(prm.raw[2] + rh * 131072 + rc * 256) : "memory");
            }
            if ((v == P_W1 && !has_w1) || (v == P_W2 && !has_w2)) continue;
            if (issued >= INFLIGHT) {
                const int sc = slot - INFLIGHT;
                mbar_wait(bar_full + (sc < 0 ? sc + NSLOT : sc) * 8, sc < 0 ? eph : eph ^ 1);
            }
            if (issued >= NSLOT) mbar_wait(bar_empty + slot * 8, eph);
            {
                const int due = (v - (!has_w2 && v > P_W2)) * TAU + toff;
                int s2 = slot - 2; uint32_t par = eph ^ 1;
                if (s2 < 0) { s2 += NSLOT; par ^= 1; }
                while ((int)(gtime32() - t0) < due) {
                    if (v > 4 && mbar_test(bar_full + s2 * 8, par)) break;
                }
            }
            const uint32_t dst = sbase + slot * TILE_B, bf = bar_full + slot * 8;
            if (v > P_W2) {
                const uint32_t bh = bar_half + (v - P_W2 - 1) * 8;
                mbar_expect_tx(bf, TILE_B / 2);
                tma_tile(dst, &prm.m[5], row, half, bf);
                mbar_expect_tx(bh, TILE_B / 2);
                tma_tile(dst + TILE_B / 2, &prm.m[5], row + 64, half, bh);
            } else {
                mbar_expect_tx(bf, TILE_B);
                tma_tile(dst, &prm.m[mi], row, half, bf);
            }
            if (++slot == NSLOT) { slot = 0; eph ^= 1; }
            issued++;
        }
    }
    int tix;
    asm volatile("mov.u32 %0, %%tid.x;" : "=r"(tix));
    if (tix == 0) return;
    const int lane = tix & 31;
    const int wix = __shfl_sync(0xffffffffu, tix >> 5, 0);
    volatile uint32_t* misc = reinterpret_cast<volatile uint32_t*>(sgen + SM_MISC);

    if (wix < 5) {
        const int gw = wix - 1;
        {
            const uint4* xr = reinterpret_cast<const uint4*>(prm.x + gw * 512);
            const uint4 u0 = __ldg(xr + lane), u1 = __ldg(xr + 32 + lane);
            const uint32_t w[8] = {u0.x, u0.y, u0.z, u0.w, u1.x, u1.y, u1.z, u1.w};
            float s = 0.f;
#pragma unroll
            for (int i = 0; i < 8; i++) s += bf_lo(w[i]) + bf_hi(w[i]);
#pragma unroll
            for (int o = 16; o; o >>= 1) s += __shfl_xor_sync(0xffffffffu, s, o);
            const float mean = s * (1.f / 512.f);
            float vs = 0.f;
#pragma unroll
            for (int i = 0; i < 8; i++) { const float d0 = bf_lo(w[i]) - mean, d1 = bf_hi(w[i]) - mean; vs += d0 * d0 + d1 * d1; }
#pragma unroll
            for (int o = 16; o; o >>= 1) vs += __shfl_xor_sync(0xffffffffu, vs, o);
            const float mb = bf16r(mean);
            float den, rden;
            asm("sqrt.approx.f32 %0, %1;" : "=f"(den) : "f"(bf16r(bf16r(vs * (1.f / 512.f)) + 1e-5f)));
            asm("rcp.approx.f32 %0, %1;" : "=f"(rden) : "f"(bf16r(den)));
            uint32_t r[8];
#pragma unroll
            for (int i = 0; i < 8; i++) r[i] = pack_bf16(bf16r(bf_lo(w[i]) - mb) * rden, bf16r(bf_hi(w[i]) - mb) * rden);
            uint8_t* xs = sgen + SM_ACT + gw * ACT_PITCH + SEG_XN + lane * 16;
            *reinterpret_cast<uint4*>(xs) = make_uint4(r[0], r[1], r[2], r[3]);
            *reinterpret_cast<uint4*>(xs + 512) = make_uint4(r[4], r[5], r[6], r[7]);
        }
        bar_arrive(BAR_XN, 448);
        float wv[4] = {1.f, 1.f, 1.f, 1.f};
        const float* pa = prm.arena + AR_Q + (hkv * 16 + gw * 4) * 512 + rhi * 128 + lane * 4;
        const float* pb = pa + 1024;
#pragma unroll 1
        for (int r = 0; r < 2; r++) {
            bar_sync(r ? BAR_VGO : BAR_QGO, 384);
            const uint32_t tag = misc[32];
            if (r == 0) mbar_wait(bar_full + QSLOT * 8, 0);
            {
                uint4 v[4];
                gather4(v, pa, pa + 512, pb, pb + 512, tag);
                const float o0 = fmaf(wv[0], asf(v[0].x), wv[1] * asf(v[1].x)) + fmaf(wv[2], asf(v[2].x), wv[3] * asf(v[3].x));
                const float o1 = fmaf(wv[0], asf(v[0].y), wv[1] * asf(v[1].y)) + fmaf(wv[2], asf(v[2].y), wv[3] * asf(v[3].y));
                const float o2 = fmaf(wv[0], asf(v[0].z), wv[1] * asf(v[1].z)) + fmaf(wv[2], asf(v[2].z), wv[3] * asf(v[3].z));
                const float o3 = fmaf(wv[0], asf(v[0].w), wv[1] * asf(v[1].w)) + fmaf(wv[2], asf(v[2].w), wv[3] * asf(v[3].w));
                *reinterpret_cast<uint2*>(sgen + SM_ACT + gw * ACT_PITCH + (r ? SEG_O : SEG_Q) + lane * 8) =
                    make_uint2(pack_bf16(o0, o1), pack_bf16(o2, o3));
                bar_arrive(r ? BAR_O : BAR_Q, 384);
            }
            if (r) break;
            bar_sync(BAR_SGO, N_SGO);
            const int rh = misc[34] & 31;
            {
                const uint32_t side = near_side(misc);
                const int o = AR_O + slot_off((rh >> 2) * 16 + gw * 4) + (rh & 3) * 128 + lane * 4;
                pa = prm.arena + pick(o, side);
                pb = prm.arena + pick(o + 2048, side);
            }
            if (rh < 28) {
                const int rg = rh;
                const float* ph = prm.arena + AR_H + ((rg >> 1) * 8 + (lane >> 4) * 4) * 512 + gw * 128 + (rg & 1) * 64 + (lane & 15) * 4;
                uint4 v[4];
                gather4(v, ph, ph + 512, ph + 1024, ph + 1536, tag);
                float4 h = sum4(v);
                h.x += __shfl_xor_sync(0xffffffffu, h.x, 16); h.y += __shfl_xor_sync(0xffffffffu, h.y, 16);
                h.z += __shfl_xor_sync(0xffffffffu, h.z, 16); h.w += __shfl_xor_sync(0xffffffffu, h.w, 16);
                if (lane < 16)
                    *reinterpret_cast<uint2*>(sgen + SM_ACT + gw * ACT_PITCH + SEG_H + lane * 8) =
                        make_uint2(pack_bf16(fmaxf(h.x, 0.f), fmaxf(h.y, 0.f)), pack_bf16(fmaxf(h.z, 0.f), fmaxf(h.w, 0.f)));
                bar_arrive(BAR_H, 384);
            }
            {
                const float* ps = prm.arena + AR_XS + ((rh >> 2) * 16 + gw * 4 + (lane & 3)) * 8 + (rh & 2) * 2;
                uint4 v = ld4(ps);
                unsigned it = 0;
                while (__any_sync(0xffffffffu, badbits(v, tag) & 3u)) { v = ld4(ps); if (++it > SPIN_LIMIT) __trap(); }
                const float m = bf_hi((rh & 1) ? v.z : v.x);
                const float l = asf((rh & 1) ? v.w : v.y);
                float M = fmaxf(m, __shfl_xor_sync(0xffffffffu, m, 1));
                M = fmaxf(M, __shfl_xor_sync(0xffffffffu, M, 2));
                const float e = ex2((m - M) * 1.4426950408889634f);
                float L = e * l;
                L += __shfl_xor_sync(0xffffffffu, L, 1);
                L += __shfl_xor_sync(0xffffffffu, L, 2);
                const float wgt = __fdividef(e, L);
#pragma unroll
                for (int i = 0; i < 4; i++) wv[i] = __shfl_sync(0xffffffffu, wgt, i);
            }
        }
        return;
    }

    if (wix == 5) {
        if (lane == 0) {
            unsigned epoch;
            asm volatile("ld.relaxed.gpu.global.u32 %0, [%1];" : "=r"(epoch) : "l"(prm.arena + AR_EPOCH) : "memory");
            misc[32] = epoch + 1;
        }
        __syncwarp();
        bar_arrive(BAR_XN, 448);
        bar_sync(BAR_RGO, 288);
        const uint32_t tg = misc[32];
        const float* pw = prm.arena + AR_XS + lane * 8;
        uint4 sw[4];
        gather4(sw, pw, pw + 256, pw + 512, pw + 768, tg);
        uint32_t n1 = 0, below = 0;
#pragma unroll
        for (int i = 0; i < 4; i++) {
            const uint32_t ones = __ballot_sync(0xffffffffu, sw[i].x & 4u);
            n1 += __popc(ones);
            below += __popc(ones & __ballot_sync(0xffffffffu, phase_key(i * 32 + lane) < phase_key(cta)));
        }
        if (lane == 0) {
            const uint32_t rank = near_side(misc) ? NCTA - n1 + below : phase_key(cta) - below;
            misc[34] = ((rank >> 6) * 2 + (rank & 1)) * 32 + ((rank & 63) >> 1);
            if (cta == 0) *reinterpret_cast<unsigned*>(prm.arena + AR_EPOCH) = (tg == 3) ? 0u : tg;
        }
        bar_arrive(BAR_SGO, N_SGO);
        return;
    }

    const int warp = wix - 6;
    const int qslot = hkv * 16 + rlo * 4 + rhi, hslot = (hkv * 2 + (cta & 1)) * 8 + ((cta >> 1) & 7);
    {
        float* pr = prm.arena + pick(AR_O + slot_off(cta) + (warp >> 1) * 128, warp & 1);
        if (lane < 4) st2(pr + lane * 2, 0u, 0u);
        bar_sync(BAR_MMA, 256);
        delay(200);
        if (lane == 0) {
            uint32_t v, c1;
            const uint32_t c0 = clock32();
            asm volatile("atom.relaxed.gpu.global.add.u32 %0, [%1], 4;" : "=r"(v) : "l"(pr) : "memory");
            asm volatile("{\n .reg .pred p;\n setp.ne.u32 p, %1, 1;\n mov.u32 %0, 0;\n @p mov.u32 %0, %%clock;\n}" : "=r"(c1) : "r"(v));
            misc[40 + warp] = c1 - c0;
        }
        __syncwarp();
    }
    const int g = lane >> 2, t = lane & 3;
    Ring ring{bar_full, bar_empty, 0, 0u};
    const int lrow = lane & 7, lmat = lane >> 3;
    const uint32_t a_lane = (lrow + ((lmat >> 1) << 3)) * 128 + ((((warp & 3) * 2 + (lmat & 1)) ^ lrow) << 4);
    const uint32_t a_off = sbase + (warp >> 2) * 8192 + a_lane;
    const uint32_t b_off = sbase + SM_ACT + (lane & 3) * ACT_PITCH + lmat * 16;
    const bool hi = t >= 2;
    const int pofs = (t & 1) * 256 + warp * 16 + g + (t >> 1) * 8;
    float* const myslot = prm.arena + slot_off(cta);
    float* cell = nullptr;
    bool has_w2 = false;
    float f0 = 0.f, f1 = 0.f, x0 = 0.f, x1 = 0.f;
    float4 pf = make_float4(0.f, 0.f, 0.f, 0.f);
    float* cell1 = nullptr;
    int oidx = 0;
    bar_sync(BAR_XN, 448);
    const uint32_t tag = misc[32];

    float vs[4] = {0.f, 0.f, 0.f, 0.f};
#pragma unroll 1
    for (int sg = 0; sg < 5; sg++) {
        if (sg == 1) {
            if (warp == 0 && lane < 4) st2(prm.arena + AR_XS + cta * 8 + lane * 2, 0u, 0u);
            if (warp == 1 && lane < 16) {
                const uint32_t base = __float_as_uint(128.f * tag);
                asm volatile("st.relaxed.gpu.global.v4.u32 [%0], {%1,%2,%2,%1};"
                             :: "l"(prm.arena + pick(AR_C + (cta >> 4) * 2048, cta >> 6) + (cta & 15) * 64 + lane * 4), "r"(base), "r"(0u) : "memory");
            }
            bar_sync(BAR_Q, 384);
            uint32_t qa[16];
            const uint8_t* qs = sgen + SM_ACT + (g & 3) * ACT_PITCH + SEG_Q + t * 4;
#pragma unroll
            for (int k = 0; k < 16; k++) qa[k] = *reinterpret_cast<const uint32_t*>(qs + k * 16);
            const uint32_t k_off = sbase + (warp * 8 + lrow) * 128;
            const uint32_t sw0 = (lmat ^ lrow) << 4, sw1 = ((lmat + 4) ^ lrow) << 4;
            float mx = -INFINITY;
            uint8_t* sdst = sgen + SM_ACT + g * ACT_PITCH + SEG_P + (warp * 8 + 2 * t) * 2;
#pragma unroll 1
            for (int it = 0; it < KT; it++) {
                ring.wait();
                const uint32_t tb = ring.slot * TILE_B + k_off;
                uint32_t b[16];
                ldsm4(tb + sw0, b); ldsm4(tb + sw1, b + 4); ldsm4(tb + 8192 + sw0, b + 8); ldsm4(tb + 8192 + sw1, b + 12);
                float c0[4] = {0.f, 0.f, 0.f, 0.f}, c1[4] = {0.f, 0.f, 0.f, 0.f};
#pragma unroll
                for (int k = 0; k < 8; k += 2) {
                    mma16816(c0, qa[2 * k], 0u, qa[2 * k + 1], 0u, b[2 * k], b[2 * k + 1]);
                    mma16816(c1, qa[2 * k + 2], 0u, qa[2 * k + 3], 0u, b[2 * k + 2], b[2 * k + 3]);
                }
                ring.release(lane);
                const float scale = 0.08838834764831845f;
                const uint32_t sp = pack_bf16(bf16r(c0[0] + c1[0]) * scale, bf16r(c0[1] + c1[1]) * scale);
                mx = fmaxf(mx, fmaxf(bf_lo(sp), bf_hi(sp)));
                if (lane < 16) *reinterpret_cast<uint32_t*>(sdst + it * 128) = sp;
            }
            mx = fmaxf(mx, __shfl_xor_sync(0xffffffffu, mx, 1));
            mx = fmaxf(mx, __shfl_xor_sync(0xffffffffu, mx, 2));
            if (lane < 16 && t == 0) reinterpret_cast<float*>(sgen + SM_WMAX)[warp * 4 + g] = mx;
            bar_sync(BAR_MMA, 256);
            const int head = warp >> 1;
            const float* wm = reinterpret_cast<const float*>(sgen + SM_WMAX) + head;
            float m = wm[0];
#pragma unroll
            for (int i = 1; i < 8; i++) m = fmaxf(m, wm[4 * i]);
            uint8_t* pp = sgen + SM_ACT + head * ACT_PITCH + SEG_P + (warp & 1) * 1024 + lane * 16;
            float l = 0.f;
#pragma unroll 1
            for (int h = 0; h < 2; h++) {
                const uint4 u = *reinterpret_cast<const uint4*>(pp + h * 512);
                uint32_t w[4] = {u.x, u.y, u.z, u.w};
#pragma unroll
                for (int i = 0; i < 4; i++) {
                    const float L2E = 1.4426950408889634f;
                    const float p0 = ex2((bf_lo(w[i]) - m) * L2E), p1 = ex2((bf_hi(w[i]) - m) * L2E);
                    l += p0 + p1;
                    w[i] = pack_bf16(p0, p1);
                }
                *reinterpret_cast<uint4*>(pp + h * 512) = make_uint4(w[0], w[1], w[2], w[3]);
            }
#pragma unroll
            for (int o = 16; o; o >>= 1) l += __shfl_xor_sync(0xffffffffu, l, o);
            if (lane == 0) reinterpret_cast<float*>(sgen + SM_LSUM)[warp] = l;
            bar_sync(BAR_MMA, 256);
            if ((warp & 1) && lane < 2) {
                const float* ls = reinterpret_cast<const float*>(sgen + SM_LSUM);
                st1(prm.arena + AR_XS + cta * 8 + head * 2 + lane, lane ? tagged(ls[warp - 1] + ls[warp], tag) : (__float_as_uint(m) | tag | (near_side(misc) << 2)));
            }
        }
        if ((sg == 2 && !has_w1) || (sg == 4 && !has_w2)) continue;
        const int i0 = (sg == 3) ? W1POS : (sg == 1) ? 0 : 32;
        const int i1 = (sg == 3) ? KT : (sg == 1) ? W1POS : (sg == 0) ? 34 : 33;
        const int seg = (sg == 0) ? SEG_XN + rhi * 256 : (sg == 2) ? SEG_XN + ((cta >> 1) & 7) * 128 : (sg == 4) ? SEG_H : SEG_P + i0 * 128;
        float* const pd = (sg == 0 ? prm.arena + AR_Q + qslot * 512 : sg == 2 ? prm.arena + AR_H + hslot * 512 : myslot + AR_O) + pofs;
        uint32_t ba = b_off + seg;
        float c0[4], c1[4];
#pragma unroll
        for (int k = 0; k < 4; k++) { c0[k] = sg == 3 ? vs[k] : 0.f; c1[k] = 0.f; }
        if (sg == 4) bar_sync(BAR_H, 384);
#pragma unroll 1
        for (int i = i0; i < i1; i++) {
            if (i == RGO) bar_arrive(BAR_RGO, 288);
            if (i == SGO) {
                bar_sync(BAR_SGO, N_SGO);
                const int role = misc[34], col = warp * 16 + g + (t >> 1) * 8;
                cell = prm.arena + pick(AR_C + (role >> 5) * 4096, role >> 6) + (col * 2 + (t & 1)) * 4;
                cell1 = other(cell) + 2048;
                oidx = (t & 1) * 1024 + (role >> 5) * 128 + col;
                has_w2 = (role & 31) < 28;
                x0 = __bfloat162float(prm.x[oidx]); x1 = __bfloat162float(prm.x[oidx + 512]);
            }
            if (i == CLRO) { st1(pd, 0u); st1(pd + 128, 0u); st1(pd + 1024, 0u); st1(pd + 1152, 0u); }
            uint32_t a[16], b[8];
            ldsm4(ba, b); ldsm4(ba + 64, b + 4);
            ring.wait();
            const uint32_t aa = a_off + ring.slot * TILE_B;
#pragma unroll
            for (int k = 0; k < 4; k++) ldsm4t(aa + k * 2048, a + 4 * k);
            mma16816(c0, a[0], a[1], a[2], a[3], b[0], b[1]);
            mma16816(c1, a[4], a[5], a[6], a[7], b[2], b[3]);
            mma16816(c0, a[8], a[9], a[10], a[11], b[4], b[5]);
            mma16816(c1, a[12], a[13], a[14], a[15], b[6], b[7]);
            ring.release(lane);
            ba += 128;
        }
        if (sg == 1) {
#pragma unroll
            for (int k = 0; k < 4; k++) vs[k] = c0[k] + c1[k];
            continue;
        }
        const float e0 = hi ? c0[2] + c1[2] : c0[0] + c1[0], e1 = hi ? c0[3] + c1[3] : c0[1] + c1[1];
        if (sg == 4) { f0 = e0; f1 = e1; pf = cell_add(cell1, e0, e1); }
        else {
            const uint32_t r0 = tagged(e0, tag), r1 = tagged(e1, tag);
            st1(pd, r0); st1(pd + 128, r1);
            if (sg == 3) { st1(pd + 1024, r0); st1(pd + 1152, r1); }
            if (sg != 2) bar_arrive(sg ? BAR_VGO : BAR_QGO, 384);
        }
    }
    {
        uint32_t a[8], b[16];
        float c[4][4];
#pragma unroll
        for (int k = 0; k < 4; k++) { c[k][0] = 0.f; c[k][1] = 0.f; c[k][2] = 0.f; c[k][3] = 0.f; }
        const uint32_t ap_off = sbase + (warp >> 2) * 4096 + a_lane;
        __nv_bfloat16* const optr = prm.out + oidx;
        uint4 fv;
        bar_sync(BAR_O, 384);
#pragma unroll
        for (int k = 0; k < 4; k++) ldsm4(b_off + SEG_O + ((k >> 1) + (k & 1) * 2) * 64, b + 4 * k);
#pragma unroll
        for (int q = 0; q < 4; q++) {
            const uint32_t bq = (q & 1) ? bar_half + (q >> 1) * 8 : ring.full + ring.slot * 8;
            const uint32_t pq = (q & 1) ? 0u : ring.phase;
            const uint32_t aa = ap_off + ring.slot * TILE_B + (q & 1) * (TILE_B / 2);
            if (q >= 2) mbar_spin(bq, pq); else mbar_wait(bq, pq);
            ldsm4t(aa, a); ldsm4t(aa + 2048, a + 4);
            if (q == 3) fv = ld4(cell1);
            mma16816(c[(2 * q) & 3], a[0], a[1], a[2], a[3], b[4 * q], b[4 * q + 1]);
            mma16816(c[(2 * q + 1) & 3], a[4], a[5], a[6], a[7], b[4 * q + 2], b[4 * q + 3]);
            if (q & 1) ring.next();
        }
        const float r0 = ((hi ? c[0][2] : c[0][0]) + (hi ? c[1][2] : c[1][0])) + ((hi ? c[2][2] : c[2][0]) + (hi ? c[3][2] : c[3][0]));
        const float r1 = ((hi ? c[0][3] : c[0][1]) + (hi ? c[1][3] : c[1][1])) + ((hi ? c[2][3] : c[2][1]) + (hi ? c[3][3] : c[3][1]));
        const float4 p = cell_add(cell, r0, r1);
        const float base = 128.f * tag;
        const float g0 = gate(asf(fv.y)), g1 = gate(asf(fv.z));
        const bool fok = asf(fv.x) == base + 28.f && asf(fv.w) == base + 28.f;
        const bool last = p.x == base + 31.f;
        if (last && fok) { optr[0] = finish(x0, p.y + r0, g0); optr[512] = finish(x1, p.z + r1, g1); }
        const bool sin = fabsf(p.x - (base + 15.5f)) < 16.f, fin = !has_w2 || fabsf(pf.x - (base + 15.5f)) < 16.f;
        if (!(sin && fin) || (last && !(fok && p.w == p.x)) || (pf.w < 0.f && pf.y == pf.z)) {
            if (!fin) cell_redo(cell1, base, f0, f1);
            const float c = sin ? p.x : cell_redo(cell, base, r0, r1);
            if (c == base + 31.f) {
                const float2 fw = cell_wait(cell1, base + 28.f);
                const float2 sv = (last && p.w == p.x) ? make_float2(p.y + r0, p.z + r1) : cell_wait(cell, base + 32.f);
                optr[0] = finish(x0, sv.x, gate(fw.x)); optr[512] = finish(x1, sv.y, gate(fw.y));
            }
        }
    }
}

typedef CUresult (*EncodeFn)(CUtensorMap*, CUtensorMapDataType, cuuint32_t, void*, const cuuint64_t*, const cuuint64_t*,
                             const cuuint32_t*, const cuuint32_t*, CUtensorMapInterleave, CUtensorMapSwizzle,
                             CUtensorMapL2promotion, CUtensorMapFloatOOBfill);

void make_map(EncodeFn enc, CUtensorMap* m, const void* base, uint64_t rows, uint64_t cols, uint32_t box_rows) {
    cuuint64_t dims[3] = {64, rows, cols / 64};
    cuuint64_t strides[2] = {cols * 2, 128};
    cuuint32_t box[3] = {64, box_rows, 2};
    cuuint32_t es[3] = {1, 1, 1};
    enc(m, CU_TENSOR_MAP_DATA_TYPE_BFLOAT16, 3, const_cast<void*>(base), dims, strides, box, es,
        CU_TENSOR_MAP_INTERLEAVE_NONE, CU_TENSOR_MAP_SWIZZLE_128B, CU_TENSOR_MAP_L2_PROMOTION_L2_256B,
        CU_TENSOR_MAP_FLOAT_OOB_FILL_NONE);
}

}

extern "C" void kernel_launch(void* const* d_in, const int* in_sizes, int n_in, void* d_out, int out_size) {
    (void)in_sizes; (void)n_in; (void)out_size;
    static EncodeFn enc = nullptr;
    static void* arena_ptr = nullptr;
    if (!enc) {
        void* fn = nullptr;
        cudaDriverEntryPointQueryResult qr;
        cudaGetDriverEntryPoint("cuTensorMapEncodeTiled", &fn, cudaEnableDefault, &qr);
        enc = (EncodeFn)fn;
        cudaGetSymbolAddress(&arena_ptr, g_arena);
        cudaFuncSetAttribute(fused_decode_kernel, cudaFuncAttributeMaxDynamicSharedMemorySize, SM_TOTAL + 1024);
    }
    Params prm;
    make_map(enc, &prm.m[0], d_in[3], 512, 4096, 64);
    make_map(enc, &prm.m[1], d_in[6], 512, 1792, 64);
    make_map(enc, &prm.m[2], d_in[1], 4ull * 8 * 16384, 128, 64);
    make_map(enc, &prm.m[3], d_in[2], 4ull * 8 * 16384, 128, 64);
    make_map(enc, &prm.m[4], d_in[7], 1792, 512, 64);
    make_map(enc, &prm.m[5], d_in[4], 4096, 512, 32);
    prm.raw[0] = (const char*)d_in[2];
    prm.raw[1] = (const char*)d_in[7];
    prm.raw[2] = (const char*)d_in[4];
    prm.raw[3] = (const char*)d_in[3];
    prm.x = (const __nv_bfloat16*)d_in[0];
    prm.out = (__nv_bfloat16*)d_out;
    prm.arena = (float*)(((uintptr_t)arena_ptr + 0x600000ull) & ~0x1fffffull);
    fused_decode_kernel<<<NCTA, NTHREADS, SM_TOTAL + 1024>>>(prm);
}
```

```cpp
#include <cuda_runtime.h>
#include <cuda_bf16.h>
#include <cuda.h>
#include <stdint.h>

namespace {

constexpr int NCTA     = 128;
constexpr int NFFN     = 112;
constexpr int NSLOT    = 13;
constexpr int TILE_B   = 16384;
constexpr int KT       = 16;
constexpr int NTHREADS = 448;

constexpr int TAU      = 655;
constexpr int LEAD     = 21;
constexpr int INFLIGHT = 8;
constexpr int W1POS    = 6;
constexpr int QSLOT = 5;
constexpr int RGO   = 4;
constexpr int SGO   = 10;
constexpr int CLRO  = 12;

constexpr int SEG_XN = 0;
constexpr int SEG_P  = 1024;
constexpr int SEG_H  = 3072;
constexpr int SEG_O  = 3200;
constexpr int SEG_Q  = 3456;
constexpr int ACT_PITCH = 3712 + 16;
constexpr int SM_ACT   = NSLOT * TILE_B;
constexpr int SM_WMAX  = SM_ACT + 4 * ACT_PITCH;
constexpr int SM_LSUM  = SM_WMAX + 128;
constexpr int SM_MISC  = SM_LSUM + 32;
constexpr int SM_BAR   = SM_MISC + 256;
constexpr int SM_TOTAL = SM_BAR + (2 * NSLOT + 8) * 8;
static_assert(SM_TOTAL + 1024 <= 232448, "smem");

constexpr int BAR_MMA = 1, BAR_XN = 2, BAR_Q = 3, BAR_H = 4, BAR_O = 5, BAR_VGO = 6, BAR_QGO = 7, BAR_SGO = 8,
              BAR_RGO = 9;
constexpr int N_SGO = 416;

__device__ __align__(4096) float g_arena[1 << 21];
constexpr int AR_O = 0, AR_C = 262144, AR_Q = 393216, AR_H = 458752;
constexpr int AR_XS = 258048;
constexpr int AR_EPOCH = AR_XS + 2048;
constexpr uint32_t HOME_MASK = (1u << 12) | (1u << 13) | (1u << 16) | (1u << 17) | (1u << 19);

struct Params {
    CUtensorMap m[6];
    const char* raw[4];
    const __nv_bfloat16* x;
    __nv_bfloat16* out;
    float* arena;
};

constexpr unsigned SPIN_LIMIT = 1u << 20;

__device__ __forceinline__ int phase_key(int cta) { return (((cta >> 2) * 13) & 31) * 4 + (cta & 3); }
__device__ __forceinline__ int slot_off(int producer) { return (producer >> 1) * 2048 + (producer & 1) * 512; }
__device__ __forceinline__ uint32_t parity(int off) { return __popc(((uint32_t)off << 2) & HOME_MASK) & 1u; }
__device__ __forceinline__ int pick(int off, uint32_t side) { return off + (int)((parity(off) ^ side) << 10); }

__device__ __forceinline__ void mbar_init(uint32_t bar, uint32_t cnt) {
    asm volatile("mbarrier.init.shared::cta.b64 [%0], %1;" :: "r"(bar), "r"(cnt) : "memory");
}
__device__ __forceinline__ void mbar_expect_tx(uint32_t bar, uint32_t bytes) {
    asm volatile("mbarrier.arrive.expect_tx.shared::cta.b64 _, [%0], %1;" :: "r"(bar), "r"(bytes) : "memory");
}
__device__ __forceinline__ void mbar_arrive(uint32_t bar) {
    asm volatile("mbarrier.arrive.shared::cta.b64 _, [%0];" :: "r"(bar) : "memory");
}
__device__ __forceinline__ bool mbar_test(uint32_t bar, uint32_t par) {
    uint32_t ok;
    asm volatile("{\n .reg .pred p;\n mbarrier.test_wait.parity.shared::cta.b64 p, [%1], %2;\n selp.u32 %0, 1, 0, p;\n}"
                 : "=r"(ok) : "r"(bar), "r"(par) : "memory");
    return ok;
}
__device__ __forceinline__ void mbar_wait(uint32_t bar, uint32_t par) {
    uint32_t ok, it = 0;
    while (true) {
        asm volatile("{\n .reg .pred p;\n mbarrier.try_wait.parity.shared::cta.b64 p, [%1], %2, %3;\n selp.u32 %0, 1, 0, p;\n}"
                     : "=r"(ok) : "r"(bar), "r"(par), "r"(10000) : "memory");
        if (ok) break;
        if (++it > SPIN_LIMIT) __trap();
    }
}
__device__ __forceinline__ void mbar_spin(uint32_t bar, uint32_t par) {
    uint32_t ok, it = 0;
    while (true) {
        asm volatile("{\n .reg .pred p;\n mbarrier.try_wait.parity.shared::cta.b64 p, [%1], %2;\n selp.u32 %0, 1, 0, p;\n}"
                     : "=r"(ok) : "r"(bar), "r"(par) : "memory");
        if (ok) break;
        if (++it > 16 * SPIN_LIMIT) __trap();
    }
}
__device__ __forceinline__ void tma_tile(uint32_t dst, const CUtensorMap* tm, int row, int half, uint32_t bar) {
    asm volatile("cp.async.bulk.tensor.3d.shared::cluster.global.mbarrier::complete_tx::bytes.L2::cache_hint [%0], [%1, {%3, %4, %5}], [%2], %6;"
                 :: "r"(dst), "l"(tm), "r"(bar), "r"(0), "r"(row), "r"(half), "l"(0x12F0000000000000ull) : "memory");
}
__device__ __forceinline__ void ldsm4(uint32_t addr, uint32_t* r) {
    asm volatile("ldmatrix.sync.aligned.m8n8.x4.shared.b16 {%0,%1,%2,%3}, [%4];"
                 : "=r"(r[0]), "=r"(r[1]), "=r"(r[2]), "=r"(r[3]) : "r"(addr) : "memory");
}
__device__ __forceinline__ void ldsm4t(uint32_t addr, uint32_t* r) {
    asm volatile("ldmatrix.sync.aligned.m8n8.x4.trans.shared.b16 {%0,%1,%2,%3}, [%4];"
                 : "=r"(r[0]), "=r"(r[1]), "=r"(r[2]), "=r"(r[3]) : "r"(addr) : "memory");
}
__device__ __forceinline__ void mma16816(float (&c)[4], uint32_t a0, uint32_t a1, uint32_t a2, uint32_t a3,
                                         uint32_t b0, uint32_t b1) {
    asm volatile("mma.sync.aligned.m16n8k16.row.col.f32.bf16.bf16.f32 {%0,%1,%2,%3}, {%4,%5,%6,%7}, {%8,%9}, {%0,%1,%2,%3};"
                 : "+f"(c[0]), "+f"(c[1]), "+f"(c[2]), "+f"(c[3])
                 : "r"(a0), "r"(a1), "r"(a2), "r"(a3), "r"(b0), "r"(b1));
}
__device__ __forceinline__ void bar_sync(int id, int n) { asm volatile("bar.sync %0, %1;" :: "r"(id), "r"(n) : "memory"); }
__device__ __forceinline__ void bar_arrive(int id, int n) { asm volatile("bar.arrive %0, %1;" :: "r"(id), "r"(n) : "memory"); }
__device__ __forceinline__ unsigned gtime32() { unsigned t; asm volatile("mov.u32 %0, %%globaltimer_lo;" : "=r"(t)); return t; }
__device__ __forceinline__ unsigned clock32() { unsigned t; asm volatile("mov.u32 %0, %%clock;" : "=r"(t)); return t; }
__device__ __forceinline__ void delay(unsigned clocks) { const unsigned c0 = clock32(); while (clock32() - c0 < clocks) {} }

__device__ __forceinline__ float bf16r(float v) {
    uint32_t d; asm("cvt.rn.bf16x2.f32 %0, %1, %2;" : "=r"(d) : "f"(v), "f"(0.f));
    return __uint_as_float(d);
}
__device__ __forceinline__ uint32_t pack_bf16(float lo, float hi) {
    uint32_t d; asm("cvt.rn.bf16x2.f32 %0, %1, %2;" : "=r"(d) : "f"(hi), "f"(lo));
    return d;
}
__device__ __forceinline__ float bf_lo(uint32_t u) { return __uint_as_float(u << 16); }
__device__ __forceinline__ float bf_hi(uint32_t u) { return __uint_as_float(u & 0xffff0000u); }
__device__ __forceinline__ float ex2(float v) { float r; asm("ex2.approx.ftz.f32 %0, %1;" : "=f"(r) : "f"(v)); return r; }
__device__ __forceinline__ float asf(uint32_t u) { return __uint_as_float(u); }

__device__ __forceinline__ uint32_t tagged(float v, uint32_t tag) { return (__float_as_uint(v) & ~3u) | tag; }
__device__ __forceinline__ void st1(float* p, uint32_t u) {
    asm volatile("st.relaxed.gpu.global.u32 [%0], %1;" :: "l"(p), "r"(u) : "memory");
}
__device__ __forceinline__ void st2(float* p, uint32_t u0, uint32_t u1) {
    asm volatile("st.relaxed.gpu.global.v2.u32 [%0], {%1, %2};" :: "l"(p), "r"(u0), "r"(u1) : "memory");
}
__device__ __forceinline__ float* other(float* p) { return reinterpret_cast<float*>(reinterpret_cast<uintptr_t>(p) ^ 4096u); }
__device__ __forceinline__ float4 cell_add(float* cell, float s, float f) {
    float4 p;
    asm volatile("atom.relaxed.gpu.global.add.v4.f32 {%0,%1,%2,%3}, [%4], {%5,%6,%7,%5};"
                 : "=f"(p.x), "=f"(p.y), "=f"(p.z), "=f"(p.w) : "l"(cell), "f"(1.f), "f"(s), "f"(f) : "memory");
    return p;
}
__device__ __forceinline__ uint4 ld4(const float* p) {
    uint4 v;
    asm volatile("ld.relaxed.gpu.global.v4.u32 {%0,%1,%2,%3}, [%4];" : "=r"(v.x), "=r"(v.y), "=r"(v.z), "=r"(v.w) : "l"(p) : "memory");
    return v;
}
__device__ __forceinline__ uint32_t badbits(const uint4& v, uint32_t tag) {
    uint32_t a, b;
    asm("lop3.b32 %0, %1, %2, %3, 0x7e;" : "=r"(a) : "r"(v.x), "r"(tag), "r"(v.y));
    asm("lop3.b32 %0, %1, %2, %3, 0x7e;" : "=r"(b) : "r"(v.z), "r"(tag), "r"(v.w));
    return a | b;
}
__device__ __forceinline__ void gather4(uint4 (&v)[4], const float* p0, const float* p1, const float* p2, const float* p3, uint32_t tag) {
    v[0] = ld4(p0); v[1] = ld4(p1); v[2] = ld4(p2); v[3] = ld4(p3);
    unsigned it = 0;
    while (true) {
        const uint32_t b0 = badbits(v[0], tag), b1 = badbits(v[1], tag), b2 = badbits(v[2], tag), b3 = badbits(v[3], tag);
        if (!__any_sync(0xffffffffu, ((b0 | b1) | (b2 | b3)) & 3u)) break;
        if (b0 & 3u) v[0] = ld4(p0);
        if (b1 & 3u) v[1] = ld4(p1);
        if (b2 & 3u) v[2] = ld4(p2);
        if (b3 & 3u) v[3] = ld4(p3);
        if (++it > SPIN_LIMIT) __trap();
    }
}
__device__ __forceinline__ float4 sum4(const uint4 (&v)[4]) {
    return make_float4((asf(v[0].x) + asf(v[1].x)) + (asf(v[2].x) + asf(v[3].x)), (asf(v[0].y) + asf(v[1].y)) + (asf(v[2].y) + asf(v[3].y)),
                       (asf(v[0].z) + asf(v[1].z)) + (asf(v[2].z) + asf(v[3].z)), (asf(v[0].w) + asf(v[1].w)) + (asf(v[2].w) + asf(v[3].w)));
}
__device__ __forceinline__ uint32_t near_side(volatile uint32_t* misc) {
    const uint32_t m0 = min(min(misc[40], misc[42]), min(misc[44], misc[46]));
    const uint32_t m1 = min(min(misc[41], misc[43]), min(misc[45], misc[47]));
    return m1 < m0;
}

__device__ __forceinline__ float gate(float f) {
    const float fr = bf16r(f);
    return bf16r(__fdividef(fr, 1.f + ex2(fr * -1.4426950408889634f)));
}
__device__ __forceinline__ __nv_bfloat16 finish(float x, float s, float g) { return __float2bfloat16_rn(x + bf16r(bf16r(s) * g)); }
__device__ __noinline__ float cell_redo(float* cell, float base, float a, float b) {
    for (unsigned it = 0; it < SPIN_LIMIT; it++) {
        const float c = asf(ld4(cell).x);
        if (c >= base && c < base + 32.f) return cell_add(cell, a, b).x;
    }
    __trap();
    return 0.f;
}
__device__ __noinline__ float2 cell_wait(const float* cell, float full) {
    for (unsigned it = 0; it < SPIN_LIMIT; it++) {
        const uint4 v = ld4(cell);
        if (asf(v.x) == full && asf(v.w) == full) return make_float2(asf(v.y), asf(v.z));
    }
    __trap();
    return make_float2(0.f, 0.f);
}

struct Ring {
    uint32_t full, empty;
    int slot; uint32_t phase;
    __device__ __forceinline__ void wait() { mbar_wait(full + slot * 8, phase); }
    __device__ __forceinline__ void next() { if (++slot == NSLOT) { slot = 0; phase ^= 1; } }
    __device__ __forceinline__ void release(int lane) {
        __syncwarp();
        if (lane == 0) mbar_arrive(empty + slot * 8);
        next();
    }
};

__global__ void __launch_bounds__(NTHREADS, 1)
fused_decode_kernel(const __grid_constant__ Params prm) {
    extern __shared__ uint8_t smem_raw[];
    const uint32_t sbase = ((uint32_t)__cvta_generic_to_shared(smem_raw) + 1023u) & ~1023u;
    uint8_t* sgen = smem_raw + (sbase - (uint32_t)__cvta_generic_to_shared(smem_raw));
    const int cta = blockIdx.x;
    const int hkv = cta >> 4, rhi = (cta >> 2) & 3, rlo = cta & 3;
    const bool has_w1 = cta < NFFN;
    const uint32_t bar_full = sbase + SM_BAR, bar_empty = bar_full + NSLOT * 8, bar_wo = bar_empty + NSLOT * 8;

    if (threadIdx.x == 161) asm volatile("prefetch.global.L2 [%0];" :: "l"(prm.raw[3] + rhi * (128 * 8192) + (hkv * 4 + rlo) * 256));
    if (threadIdx.x - 1u < 31u) return;
    if (threadIdx.x == 0) {
        const unsigned t0 = gtime32();
        mbar_init(bar_full, 1);
        asm volatile("fence.mbarrier_init.release.cluster;" ::: "memory");
        mbar_expect_tx(bar_full, TILE_B);
        tma_tile(sbase, &prm.m[0], rhi * 128, (hkv * 4 + rlo) * 2, bar_full);
#pragma unroll
        for (int i = 1; i < 2 * NSLOT + 8; i++) mbar_init(bar_full + i * 8, (i < NSLOT || i >= 2 * NSLOT) ? 1 : 8);
        asm volatile("fence.mbarrier_init.release.cluster;" ::: "memory");
        volatile uint32_t* prole = reinterpret_cast<volatile uint32_t*>(sgen + SM_MISC) + 34;
        *prole = 0xffffffffu;
        asm volatile("barrier.arrive %0, %1;" :: "n"(BAR_XN), "n"(448) : "memory");
        const int kvrow = (rhi * 8 + hkv) * 16384 + 12288 + (rlo & 1) * 64 + (rlo >> 1) * 256;
        const int toff = ((phase_key(cta) >> 2) * TAU) / 32 - (LEAD * TAU) / 16;
        constexpr int P_W1 = 18 + W1POS, P_W2 = 35, P_END = 38;
        int slot = 1; uint32_t eph = 1;
        int issued = 1;
        uint32_t role = 0;
#pragma unroll 1
        for (int v = 1; v < P_END; v++) {
            if (v == 31) {
                unsigned it = 0;
                while ((role = *prole) == 0xffffffffu) { if (++it > 16 * SPIN_LIMIT) __trap(); }
            }
            const int rh = role & 31, rc = role >> 5;
            const bool has_w2 = rh < 28;
            int mi, row, half;
            if (v == 1)          { mi = 0; row = rhi * 128 + 64; half = (hkv * 4 + rlo) * 2; }
            else if (v == P_W1)  { mi = 1; row = ((cta >> 1) & 7) * 64; half = (hkv * 2 + (cta & 1)) * 2; }
            else if (v < P_W2)   { const int j = v - 2 - (v > P_W1); mi = 2 + (j >> 4); row = kvrow + (j & 1) * 128 + ((j & 15) >> 1) * 512; half = 0; }
            else if (v == P_W2)  { mi = 4; row = rh * 64; half = rc * 2; }
            else                 { mi = 5; row = rh * 128 + (v - P_W2 - 1) * 32; half = rc * 2; }
            if (v < 6) asm volatile("prefetch.tensormap [%0];" :: "l"(&prm.m[v]) : "memory");
            if (v == 10) asm volatile("cp.async.bulk.prefetch.L2.global [%0], 128;" :: "l"(prm.raw[0] + (size_t)kvrow * 256) : "memory");
            if (v == 31) {
                if (has_w2) asm volatile("cp.async.bulk.prefetch.L2.global [%0], 128;" :: "l"(prm.raw[1] + rh * 65536 + rc * 256) : "memory");
                asm volatile("cp.async.bulk.prefetch.L2.global [%0], 128;" :: "l"(prm.raw[2] + rh * 131072 + rc * 256) : "memory");
            }
            if ((v == P_W1 && !has_w1) || (v == P_W2 && !has_w2)) continue;
            if (issued >= INFLIGHT) {
                const int sc = slot - INFLIGHT;
                mbar_wait(bar_full + (sc < 0 ? sc + NSLOT : sc) * 8, sc < 0 ? eph : eph ^ 1);
            }
            if (issued >= NSLOT) mbar_wait(bar_empty + slot * 8, eph);
            {
                const int due = (v - (!has_w2 && v > P_W2)) * TAU + toff;
                int s2 = slot - 2; uint32_t par = eph ^ 1;
                if (s2 < 0) { s2 += NSLOT; par ^= 1; }
                while ((int)(gtime32() - t0) < due) {
                    if (v > 4 && mbar_test(bar_full + s2 * 8, par)) break;
                }
            }
            const uint32_t dst = sbase + slot * TILE_B, bf = bar_full + slot * 8;
            if (v > P_W2) {
#pragma unroll
                for (int q = 0; q < 4; q++) {
                    const int piece = (q & 1) * 2 + (q >> 1);
                    const uint32_t bp = bar_wo + ((v - P_W2 - 1) * 4 + piece) * 8;
                    mbar_expect_tx(bp, TILE_B / 4);
                    tma_tile(dst + piece * (TILE_B / 4), &prm.m[5], row + (q & 1) * 64, half + (q >> 1), bp);
                }
            } else {
                mbar_expect_tx(bf, TILE_B);
                tma_tile(dst, &prm.m[mi], row, half, bf);
            }
            if (++slot == NSLOT) { slot = 0; eph ^= 1; }
            issued++;
        }
    }
    int tix;
    asm volatile("mov.u32 %0, %%tid.x;" : "=r"(tix));
    if (tix == 0) return;
    const int lane = tix & 31;
    const int wix = __shfl_sync(0xffffffffu, tix >> 5, 0);
    volatile uint32_t* misc = reinterpret_cast<volatile uint32_t*>(sgen + SM_MISC);

    if (wix < 5) {
        const int gw = wix - 1;
        {
            const uint4* xr = reinterpret_cast<const uint4*>(prm.x + gw * 512);
            const uint4 u0 = __ldg(xr + lane), u1 = __ldg(xr + 32 + lane);
            const uint32_t w[8] = {u0.x, u0.y, u0.z, u0.w, u1.x, u1.y, u1.z, u1.w};
            float s = 0.f;
#pragma unroll
            for (int i = 0; i < 8; i++) s += bf_lo(w[i]) + bf_hi(w[i]);
#pragma unroll
            for (int o = 16; o; o >>= 1) s += __shfl_xor_sync(0xffffffffu, s, o);
            const float mean = s * (1.f / 512.f);
            float vs = 0.f;
#pragma unroll
            for (int i = 0; i < 8; i++) { const float d0 = bf_lo(w[i]) - mean, d1 = bf_hi(w[i]) - mean; vs += d0 * d0 + d1 * d1; }
#pragma unroll
            for (int o = 16; o; o >>= 1) vs += __shfl_xor_sync(0xffffffffu, vs, o);
            const float mb = bf16r(mean);
            float den, rden;
            asm("sqrt.approx.f32 %0, %1;" : "=f"(den) : "f"(bf16r(bf16r(vs * (1.f / 512.f)) + 1e-5f)));
            asm("rcp.approx.f32 %0, %1;" : "=f"(rden) : "f"(bf16r(den)));
            uint32_t r[8];
#pragma unroll
            for (int i = 0; i < 8; i++) r[i] = pack_bf16(bf16r(bf_lo(w[i]) - mb) * rden, bf16r(bf_hi(w[i]) - mb) * rden);
            uint8_t* xs = sgen + SM_ACT + gw * ACT_PITCH + SEG_XN + lane * 16;
            *reinterpret_cast<uint4*>(xs) = make_uint4(r[0], r[1], r[2], r[3]);
            *reinterpret_cast<uint4*>(xs + 512) = make_uint4(r[4], r[5], r[6], r[7]);
        }
        bar_arrive(BAR_XN, 448);
        float wv[4] = {1.f, 1.f, 1.f, 1.f};
        const float* pa = prm.arena + AR_Q + (hkv * 16 + gw * 4) * 512 + rhi * 128 + lane * 4;
        const float* pb = pa + 1024;
#pragma unroll 1
        for (int r = 0; r < 2; r++) {
            bar_sync(r ? BAR_VGO : BAR_QGO, 384);
            const uint32_t tag = misc[32];
            if (r == 0) mbar_wait(bar_full + QSLOT * 8, 0);
            {
                uint4 v[4];
                gather4(v, pa, pa + 512, pb, pb + 512, tag);
                const float o0 = fmaf(wv[0], asf(v[0].x), wv[1] * asf(v[1].x)) + fmaf(wv[2], asf(v[2].x), wv[3] * asf(v[3].x));
                const float o1 = fmaf(wv[0], asf(v[0].y), wv[1] * asf(v[1].y)) + fmaf(wv[2], asf(v[2].y), wv[3] * asf(v[3].y));
                const float o2 = fmaf(wv[0], asf(v[0].z), wv[1] * asf(v[1].z)) + fmaf(wv[2], asf(v[2].z), wv[3] * asf(v[3].z));
                const float o3 = fmaf(wv[0], asf(v[0].w), wv[1] * asf(v[1].w)) + fmaf(wv[2], asf(v[2].w), wv[3] * asf(v[3].w));
                *reinterpret_cast<uint2*>(sgen + SM_ACT + gw * ACT_PITCH + (r ? SEG_O : SEG_Q) + lane * 8) =
                    make_uint2(pack_bf16(o0, o1), pack_bf16(o2, o3));
                bar_arrive(r ? BAR_O : BAR_Q, 384);
            }
            if (r) break;
            bar_sync(BAR_SGO, N_SGO);
            const int rh = misc[34] & 31;
            {
                const uint32_t side = near_side(misc);
                const int o = AR_O + slot_off((rh >> 2) * 16 + gw * 4) + (rh & 3) * 128 + lane * 4;
                pa = prm.arena + pick(o, side);
                pb = prm.arena + pick(o + 2048, side);
            }
            if (rh < 28) {
                const int rg = rh;
                const float* ph = prm.arena + AR_H + ((rg >> 1) * 8 + (lane >> 4) * 4) * 512 + gw * 128 + (rg & 1) * 64 + (lane & 15) * 4;
                uint4 v[4];
                gather4(v, ph, ph + 512, ph + 1024, ph + 1536, tag);
                float4 h = sum4(v);
                h.x += __shfl_xor_sync(0xffffffffu, h.x, 16); h.y += __shfl_xor_sync(0xffffffffu, h.y, 16);
                h.z += __shfl_xor_sync(0xffffffffu, h.z, 16); h.w += __shfl_xor_sync(0xffffffffu, h.w, 16);
                if (lane < 16)
                    *reinterpret_cast<uint2*>(sgen + SM_ACT + gw * ACT_PITCH + SEG_H + lane * 8) =
                        make_uint2(pack_bf16(fmaxf(h.x, 0.f), fmaxf(h.y, 0.f)), pack_bf16(fmaxf(h.z, 0.f), fmaxf(h.w, 0.f)));
                bar_arrive(BAR_H, 384);
            }
            {
                const float* ps = prm.arena + AR_XS + ((rh >> 2) * 16 + gw * 4 + (lane & 3)) * 8 + (rh & 2) * 2;
                uint4 v = ld4(ps);
                unsigned it = 0;
                while (__any_sync(0xffffffffu, badbits(v, tag) & 3u)) { v = ld4(ps); if (++it > SPIN_LIMIT) __trap(); }
                const float m = bf_hi((rh & 1) ? v.z : v.x);
                const float l = asf((rh & 1) ? v.w : v.y);
                float M = fmaxf(m, __shfl_xor_sync(0xffffffffu, m, 1));
                M = fmaxf(M, __shfl_xor_sync(0xffffffffu, M, 2));
                const float e = ex2((m - M) * 1.4426950408889634f);
                float L = e * l;
                L += __shfl_xor_sync(0xffffffffu, L, 1);
                L += __shfl_xor_sync(0xffffffffu, L, 2);
                const float wgt = __fdividef(e, L);
#pragma unroll
                for (int i = 0; i < 4; i++) wv[i] = __shfl_sync(0xffffffffu, wgt, i);
            }
        }
        return;
    }

    if (wix == 5) {
        if (lane == 0) {
            unsigned epoch;
            asm volatile("ld.relaxed.gpu.global.u32 %0, [%1];" : "=r"(epoch) : "l"(prm.arena + AR_EPOCH) : "memory");
            misc[32] = epoch + 1;
        }
        __syncwarp();
        bar_arrive(BAR_XN, 448);
        bar_sync(BAR_RGO, 288);
        const uint32_t tg = misc[32];
        const float* pw = prm.arena + AR_XS + lane * 8;
        uint4 sw[4];
        gather4(sw, pw, pw + 256, pw + 512, pw + 768, tg);
        uint32_t n1 = 0, below = 0;
#pragma unroll
        for (int i = 0; i < 4; i++) {
            const uint32_t ones = __ballot_sync(0xffffffffu, sw[i].x & 4u);
            n1 += __popc(ones);
            below += __popc(ones & __ballot_sync(0xffffffffu, phase_key(i * 32 + lane) < phase_key(cta)));
        }
        if (lane == 0) {
            const uint32_t rank = near_side(misc) ? NCTA - n1 + below : phase_key(cta) - below;
            misc[34] = ((rank >> 6) * 2 + (rank & 1)) * 32 + ((rank & 63) >> 1);
            if (cta == 0) *reinterpret_cast<unsigned*>(prm.arena + AR_EPOCH) = (tg == 3) ? 0u : tg;
        }
        bar_arrive(BAR_SGO, N_SGO);
        return;
    }

    const int warp = wix - 6;
    const int qslot = hkv * 16 + rlo * 4 + rhi, hslot = (hkv * 2 + (cta & 1)) * 8 + ((cta >> 1) & 7);
    {
        float* pr = prm.arena + pick(AR_O + slot_off(cta) + (warp >> 1) * 128, warp & 1);
        if (lane < 4) st2(pr + lane * 2, 0u, 0u);
        bar_sync(BAR_MMA, 256);
        delay(200);
        if (lane == 0) {
            uint32_t v, c1;
            const uint32_t c0 = clock32();
            asm volatile("atom.relaxed.gpu.global.add.u32 %0, [%1], 4;" : "=r"(v) : "l"(pr) : "memory");
            asm volatile("{\n .reg .pred p;\n setp.ne.u32 p, %1, 1;\n mov.u32 %0, 0;\n @p mov.u32 %0, %%clock;\n}" : "=r"(c1) : "r"(v));
            misc[40 + warp] = c1 - c0;
        }
        __syncwarp();
    }
    const int g = lane >> 2, t = lane & 3;
    Ring ring{bar_full, bar_empty, 0, 0u};
    const int lrow = lane & 7, lmat = lane >> 3;
    const uint32_t a_lane = (lrow + ((lmat >> 1) << 3)) * 128 + ((((warp & 3) * 2 + (lmat & 1)) ^ lrow) << 4);
    const uint32_t a_off = sbase + (warp >> 2) * 8192 + a_lane;
    const uint32_t b_off = sbase + SM_ACT + (lane & 3) * ACT_PITCH + lmat * 16;
    const bool hi = t >= 2;
    const int pofs = (t & 1) * 256 + warp * 16 + g + (t >> 1) * 8;
    float* const myslot = prm.arena + slot_off(cta);
    float* cell = nullptr;
    bool has_w2 = false;
    float f0 = 0.f, f1 = 0.f, x0 = 0.f, x1 = 0.f;
    float4 pf = make_float4(0.f, 0.f, 0.f, 0.f);
    float* cell1 = nullptr;
    int oidx = 0;
    bar_sync(BAR_XN, 448);
    const uint32_t tag = misc[32];

    float vs[4] = {0.f, 0.f, 0.f, 0.f};
#pragma unroll 1
    for (int sg = 0; sg < 5; sg++) {
        if (sg == 1) {
            if (warp == 0 && lane < 4) st2(prm.arena + AR_XS + cta * 8 + lane * 2, 0u, 0u);
            if (warp == 1 && lane < 16) {
                const uint32_t base = __float_as_uint(128.f * tag);
                asm volatile("st.relaxed.gpu.global.v4.u32 [%0], {%1,%2,%2,%1};"
                             :: "l"(prm.arena + pick(AR_C + (cta >> 4) * 2048, cta >> 6) + (cta & 15) * 64 + lane * 4), "r"(base), "r"(0u) : "memory");
            }
            bar_sync(BAR_Q, 384);
            uint32_t qa[16];
            const uint8_t* qs = sgen + SM_ACT + (g & 3) * ACT_PITCH + SEG_Q + t * 4;
#pragma unroll
            for (int k = 0; k < 16; k++) qa[k] = *reinterpret_cast<const uint32_t*>(qs + k * 16);
            const uint32_t k_off = sbase + (warp * 8 + lrow) * 128;
            const uint32_t sw0 = (lmat ^ lrow) << 4, sw1 = ((lmat + 4) ^ lrow) << 4;
            float mx = -INFINITY;
            uint8_t* sdst = sgen + SM_ACT + g * ACT_PITCH + SEG_P + (warp * 8 + 2 * t) * 2;
#pragma unroll 1
            for (int it = 0; it < KT; it++) {
                ring.wait();
                const uint32_t tb = ring.slot * TILE_B + k_off;
                uint32_t b[16];
                ldsm4(tb + sw0, b); ldsm4(tb + sw1, b + 4); ldsm4(tb + 8192 + sw0, b + 8); ldsm4(tb + 8192 + sw1, b + 12);
                float c0[4] = {0.f, 0.f, 0.f, 0.f}, c1[4] = {0.f, 0.f, 0.f, 0.f};
#pragma unroll
                for (int k = 0; k < 8; k += 2) {
                    mma16816(c0, qa[2 * k], 0u, qa[2 * k + 1], 0u, b[2 * k], b[2 * k + 1]);
                    mma16816(c1, qa[2 * k + 2], 0u, qa[2 * k + 3], 0u, b[2 * k + 2], b[2 * k + 3]);
                }
                ring.release(lane);
                const float scale = 0.08838834764831845f;
                const uint32_t sp = pack_bf16(bf16r(c0[0] + c1[0]) * scale, bf16r(c0[1] + c1[1]) * scale);
                mx = fmaxf(mx, fmaxf(bf_lo(sp), bf_hi(sp)));
                if (lane < 16) *reinterpret_cast<uint32_t*>(sdst + it * 128) = sp;
            }
            mx = fmaxf(mx, __shfl_xor_sync(0xffffffffu, mx, 1));
            mx = fmaxf(mx, __shfl_xor_sync(0xffffffffu, mx, 2));
            if (lane < 16 && t == 0) reinterpret_cast<float*>(sgen + SM_WMAX)[warp * 4 + g] = mx;
            bar_sync(BAR_MMA, 256);
            const int head = warp >> 1;
            const float* wm = reinterpret_cast<const float*>(sgen + SM_WMAX) + head;
            float m = wm[0];
#pragma unroll
            for (int i = 1; i < 8; i++) m = fmaxf(m, wm[4 * i]);
            uint8_t* pp = sgen + SM_ACT + head * ACT_PITCH + SEG_P + (warp & 1) * 1024 + lane * 16;
            float l = 0.f;
#pragma unroll 1
            for (int h = 0; h < 2; h++) {
                const uint4 u = *reinterpret_cast<const uint4*>(pp + h * 512);
                uint32_t w[4] = {u.x, u.y, u.z, u.w};
#pragma unroll
                for (int i = 0; i < 4; i++) {
                    const float L2E = 1.4426950408889634f;
                    const float p0 = ex2((bf_lo(w[i]) - m) * L2E), p1 = ex2((bf_hi(w[i]) - m) * L2E);
                    l += p0 + p1;
                    w[i] = pack_bf16(p0, p1);
                }
                *reinterpret_cast<uint4*>(pp + h * 512) = make_uint4(w[0], w[1], w[2], w[3]);
            }
#pragma unroll
            for (int o = 16; o; o >>= 1) l += __shfl_xor_sync(0xffffffffu, l, o);
            if (lane == 0) reinterpret_cast<float*>(sgen + SM_LSUM)[warp] = l;
            bar_sync(BAR_MMA, 256);
            if ((warp & 1) && lane < 2) {
                const float* ls = reinterpret_cast<const float*>(sgen + SM_LSUM);
                st1(prm.arena + AR_XS + cta * 8 + head * 2 + lane, lane ? tagged(ls[warp - 1] + ls[warp], tag) : (__float_as_uint(m) | tag | (near_side(misc) << 2)));
            }
        }
        if ((sg == 2 && !has_w1) || (sg == 4 && !has_w2)) continue;
        const int i0 = (sg == 3) ? W1POS : (sg == 1) ? 0 : 32;
        const int i1 = (sg == 3) ? KT : (sg == 1) ? W1POS : (sg == 0) ? 34 : 33;
        const int seg = (sg == 0) ? SEG_XN + rhi * 256 : (sg == 2) ? SEG_XN + ((cta >> 1) & 7) * 128 : (sg == 4) ? SEG_H : SEG_P + i0 * 128;
        float* const pd = (sg == 0 ? prm.arena + AR_Q + qslot * 512 : sg == 2 ? prm.arena + AR_H + hslot * 512 : myslot + AR_O) + pofs;
        uint32_t ba = b_off + seg;
        float c0[4], c1[4];
#pragma unroll
        for (int k = 0; k < 4; k++) { c0[k] = sg == 3 ? vs[k] : 0.f; c1[k] = 0.f; }
        if (sg == 4) bar_sync(BAR_H, 384);
#pragma unroll 1
        for (int i = i0; i < i1; i++) {
            if (i == RGO) bar_arrive(BAR_RGO, 288);
            if (i == SGO) {
                bar_sync(BAR_SGO, N_SGO);
                const int role = misc[34], col = warp * 16 + g + (t >> 1) * 8;
                cell = prm.arena + pick(AR_C + (role >> 5) * 4096, role >> 6) + (col * 2 + (t & 1)) * 4;
                cell1 = other(cell) + 2048;
                oidx = (t & 1) * 1024 + (role >> 5) * 128 + col;
                has_w2 = (role & 31) < 28;
                x0 = __bfloat162float(prm.x[oidx]); x1 = __bfloat162float(prm.x[oidx + 512]);
            }
            if (i == CLRO) { st1(pd, 0u); st1(pd + 128, 0u); st1(pd + 1024, 0u); st1(pd + 1152, 0u); }
            uint32_t a[16], b[8];
            ldsm4(ba, b); ldsm4(ba + 64, b + 4);
            ring.wait();
            const uint32_t aa = a_off + ring.slot * TILE_B;
#pragma unroll
            for (int k = 0; k < 4; k++) ldsm4t(aa + k * 2048, a + 4 * k);
            mma16816(c0, a[0], a[1], a[2], a[3], b[0], b[1]);
            mma16816(c1, a[4], a[5], a[6], a[7], b[2], b[3]);
            mma16816(c0, a[8], a[9], a[10], a[11], b[4], b[5]);
            mma16816(c1, a[12], a[13], a[14], a[15], b[6], b[7]);
            ring.release(lane);
            ba += 128;
        }
        if (sg == 1) {
#pragma unroll
            for (int k = 0; k < 4; k++) vs[k] = c0[k] + c1[k];
            continue;
        }
        const float e0 = hi ? c0[2] + c1[2] : c0[0] + c1[0], e1 = hi ? c0[3] + c1[3] : c0[1] + c1[1];
        if (sg == 4) { f0 = e0; f1 = e1; pf = cell_add(cell1, e0, e1); }
        else {
            const uint32_t r0 = tagged(e0, tag), r1 = tagged(e1, tag);
            st1(pd, r0); st1(pd + 128, r1);
            if (sg == 3) { st1(pd + 1024, r0); st1(pd + 1152, r1); }
            if (sg != 2) bar_arrive(sg ? BAR_VGO : BAR_QGO, 384);
        }
    }
    {
        uint32_t a[8], b[16];
        float c[4][4];
#pragma unroll
        for (int k = 0; k < 4; k++) { c[k][0] = 0.f; c[k][1] = 0.f; c[k][2] = 0.f; c[k][3] = 0.f; }
        const uint32_t ap_off = sbase + (warp >> 2) * 4096 + a_lane;
        __nv_bfloat16* const optr = prm.out + oidx;
        uint4 fv;
        bar_sync(BAR_O, 384);
#pragma unroll
        for (int k = 0; k < 4; k++) ldsm4(b_off + SEG_O + ((k >> 1) + (k & 1) * 2) * 64, b + 4 * k);
#pragma unroll
        for (int q = 0; q < 4; q++) {
            const uint32_t bq = bar_wo + (q * 2 + (warp >> 2)) * 8;
            const uint32_t aa = ap_off + ring.slot * TILE_B + (q & 1) * (TILE_B / 2);
            if (q >= 2) mbar_spin(bq, 0u); else mbar_wait(bq, 0u);
            ldsm4t(aa, a); ldsm4t(aa + 2048, a + 4);
            if (q == 3) fv = ld4(cell1);
            mma16816(c[(2 * q) & 3], a[0], a[1], a[2], a[3], b[4 * q], b[4 * q + 1]);
            mma16816(c[(2 * q + 1) & 3], a[4], a[5], a[6], a[7], b[4 * q + 2], b[4 * q + 3]);
            if (q & 1) ring.next();
        }
        const float r0 = ((hi ? c[0][2] : c[0][0]) + (hi ? c[1][2] : c[1][0])) + ((hi ? c[2][2] : c[2][0]) + (hi ? c[3][2] : c[3][0]));
        const float r1 = ((hi ? c[0][3] : c[0][1]) + (hi ? c[1][3] : c[1][1])) + ((hi ? c[2][3] : c[2][1]) + (hi ? c[3][3] : c[3][1]));
        const float4 p = cell_add(cell, r0, r1);
        const float base = 128.f * tag;
        const float g0 = gate(asf(fv.y)), g1 = gate(asf(fv.z));
        const bool fok = asf(fv.x) == base + 28.f && asf(fv.w) == base + 28.f;
        const bool last = p.x == base + 31.f;
        if (last && fok) { optr[0] = finish(x0, p.y + r0, g0); optr[512] = finish(x1, p.z + r1, g1); }
        const bool sin = fabsf(p.x - (base + 15.5f)) < 16.f, fin = !has_w2 || fabsf(pf.x - (base + 15.5f)) < 16.f;
        if (!(sin && fin) || (last && !(fok && p.w == p.x)) || (pf.w < 0.f && pf.y == pf.z)) {
            if (!fin) cell_redo(cell1, base, f0, f1);
            const float c = sin ? p.x : cell_redo(cell, base, r0, r1);
            if (c == base + 31.f) {
                const float2 fw = cell_wait(cell1, base + 28.f);
                const float2 sv = (last && p.w == p.x) ? make_float2(p.y + r0, p.z + r1) : cell_wait(cell, base + 32.f);
                optr[0] = finish(x0, sv.x, gate(fw.x)); optr[512] = finish(x1, sv.y, gate(fw.y));
            }
        }
    }
}

typedef CUresult (*EncodeFn)(CUtensorMap*, CUtensorMapDataType, cuuint32_t, void*, const cuuint64_t*, const cuuint64_t*,
                             const cuuint32_t*, const cuuint32_t*, CUtensorMapInterleave, CUtensorMapSwizzle,
                             CUtensorMapL2promotion, CUtensorMapFloatOOBfill);

void make_map(EncodeFn enc, CUtensorMap* m, const void* base, uint64_t rows, uint64_t cols, uint32_t box_rows, uint32_t box_halves) {
    cuuint64_t dims[3] = {64, rows, cols / 64};
    cuuint64_t strides[2] = {cols * 2, 128};
    cuuint32_t box[3] = {64, box_rows, box_halves};
    cuuint32_t es[3] = {1, 1, 1};
    enc(m, CU_TENSOR_MAP_DATA_TYPE_BFLOAT16, 3, const_cast<void*>(base), dims, strides, box, es,
        CU_TENSOR_MAP_INTERLEAVE_NONE, CU_TENSOR_MAP_SWIZZLE_128B, CU_TENSOR_MAP_L2_PROMOTION_L2_256B,
        CU_TENSOR_MAP_FLOAT_OOB_FILL_NONE);
}

}

extern "C" void kernel_launch(void* const* d_in, const int* in_sizes, int n_in, void* d_out, int out_size) {
    (void)in_sizes; (void)n_in; (void)out_size;
    static EncodeFn enc = nullptr;
    static void* arena_ptr = nullptr;
    if (!enc) {
        void* fn = nullptr;
        cudaDriverEntryPointQueryResult qr;
        cudaGetDriverEntryPoint("cuTensorMapEncodeTiled", &fn, cudaEnableDefault, &qr);
        enc = (EncodeFn)fn;
        cudaGetSymbolAddress(&arena_ptr, g_arena);
        cudaFuncSetAttribute(fused_decode_kernel, cudaFuncAttributeMaxDynamicSharedMemorySize, SM_TOTAL + 1024);
    }
    Params prm;
    make_map(enc, &prm.m[0], d_in[3], 512, 4096, 64, 2);
    make_map(enc, &prm.m[1], d_in[6], 512, 1792, 64, 2);
    make_map(enc, &prm.m[2], d_in[1], 4ull * 8 * 16384, 128, 64, 2);
    make_map(enc, &prm.m[3], d_in[2], 4ull * 8 * 16384, 128, 64, 2);
    make_map(enc, &prm.m[4], d_in[7], 1792, 512, 64, 2);
    make_map(enc, &prm.m[5], d_in[4], 4096, 512, 32, 1);
    prm.raw[0] = (const char*)d_in[2];
    prm.raw[1] = (const char*)d_in[7];
    prm.raw[2] = (const char*)d_in[4];
    prm.raw[3] = (const char*)d_in[3];
    prm.x = (const __nv_bfloat16*)d_in[0];
    prm.out = (__nv_bfloat16*)d_out;
    prm.arena = (float*)(((uintptr_t)arena_ptr + 0x600000ull) & ~0x1fffffull);
    fused_decode_kernel<<<NCTA, NTHREADS, SM_TOTAL + 1024>>>(prm);
}
```
